```python
import torch

def _softmax(x, axis=-1):
    return torch.softmax(x, dim=axis)

def _gelu(x):
    return torch.nn.functional.gelu(x, approximate='tanh')

def _silu(x):
    return torch.nn.functional.silu(x)

def _sigmoid(x):
    return torch.sigmoid(x)

def _layernorm(x, axis=-1, eps=1e-05):
    m = x.mean(dim=axis, keepdim=True)
    v = x.var(dim=axis, keepdim=True, unbiased=False)
    return (x - m) / torch.sqrt(v + eps)

def _scatter_add(tgt, idx, src, axis=0):
    return tgt.clone().index_add_(axis, idx, src)

def _segment_sum(src, seg, n):
    out = torch.zeros((n,) + src.shape[1:], dtype=src.dtype)
    return out.index_add_(0, seg, src)

def _pad(x, pw):
    flat = tuple((v for pair in reversed(pw) for v in pair))
    return torch.nn.functional.pad(x, flat)
kernel_name = 'adaLN_cond__memory_aug_recurrent_mem_tr__moe_arch_mod__prompt'

def setup_inputs():

    _w = lambda a: (lambda t: t.to(torch.bfloat16) if t.is_floating_point() else t)(torch.as_tensor(a))

    def _A_setup():
        B, S, Dm = (1, 2048, 512)
        H, Dh = (32, 128)
        M, seg = (8, 32)
        seg = min(seg, S)
        S = S // seg * seg
        return {'x': _w((lambda *s: torch.randn(*s, dtype=torch.bfloat16) * 0.05)(B, S, Dm)), 'mem0': _w((lambda *s: torch.randn(*s, dtype=torch.bfloat16) * 0.4)(B, M, Dm)), 'Wq': _w((lambda *s: torch.randn(*s, dtype=torch.bfloat16) * 3.2)(Dm, H, Dh) * Dm ** (-0.5)), 'Wk': _w((lambda *s: torch.randn(*s, dtype=torch.bfloat16) * 3.2)(Dm, H, Dh) * Dm ** (-0.5)), 'Wv': _w((lambda *s: torch.randn(*s, dtype=torch.bfloat16) * 0.4)(Dm, H, Dh) * Dm ** (-0.5)), 'Wo': _w((lambda *s: torch.randn(*s, dtype=torch.bfloat16) * 0.4)(H, Dh, Dm) * (H * Dh) ** (-0.5)), 'seg_len': seg}
    _A_in = _A_setup()

    def _B_setup():
        B, S, D, F, C = (1, 2048, 512, 1376, 2)
        return {'x': _w((lambda *s: torch.randn(*s, dtype=torch.bfloat16) * 0.05)(B, S, D)), 'w_r': _w((lambda *s: torch.randn(*s, dtype=torch.bfloat16) * 0.05)(D)), 'w_gate': _w((lambda *s: torch.randn(*s, dtype=torch.bfloat16) * 0.05)(D, F)), 'w_up': _w((lambda *s: torch.randn(*s, dtype=torch.bfloat16) * 0.05)(D, F)), 'w_down': _w((lambda *s: torch.randn(*s, dtype=torch.bfloat16) * 0.05)(F, D))}
    _B_in = _B_setup()
    return {'A_x': _A_in['x'], 'A_mem0': _A_in['mem0'], 'A_Wq': _A_in['Wq'], 'A_Wk': _A_in['Wk'], 'A_Wv': _A_in['Wv'], 'A_Wo': _A_in['Wo'], 'A_seg_len': _A_in['seg_len'], 'B_x': _B_in['x'], 'B_w_r': _B_in['w_r'], 'B_w_gate': _B_in['w_gate'], 'B_w_up': _B_in['w_up'], 'B_w_down': _B_in['w_down'], 'c': _w((lambda *s: torch.randn(*s, dtype=torch.bfloat16) * 0.05)(1, 512) * 8.0), 'w_mod': _w((lambda *s: torch.randn(*s, dtype=torch.bfloat16) * 0.05)(512, 6 * 512) * 512 ** (-0.5) * 8.0)}

def reference(A_x, A_mem0, A_Wq, A_Wk, A_Wv, A_Wo, A_seg_len, B_x, B_w_r, B_w_gate, B_w_up, B_w_down, c, w_mod):

    def _A_ref(x, mem0, Wq, Wk, Wv, Wo, seg_len):
        B, S, Dm = x.shape
        H, Dh = (Wq.shape[1], Wq.shape[2])
        M = mem0.shape[1]
        scale = Dh ** (-0.5)
        n_seg = S // seg_len
        L = M + seg_len
        idx = torch.arange(L)
        mask = (idx[:, None] < M) | (idx[:, None] >= idx[None, :])
        mem = mem0
        outs = []
        for s in range(n_seg):
            xs = x[:, s * seg_len:(s + 1) * seg_len, :].clone()
            h = torch.concatenate([mem, xs], axis=1)
            q = torch.einsum('btd,dhe->bhte', h, Wq)
            k = torch.einsum('btd,dhe->bhte', h, Wk)
            v = torch.einsum('btd,dhe->bhte', h, Wv)
            scores = torch.einsum('bhqe,bhke->bhqk', q, k) * scale
            scores = torch.where(mask[None, None], scores, -1000000000.0)
            p = _softmax(scores, axis=-1)
            o = torch.einsum('bhqk,bhke->bhqe', p, v)
            o = torch.einsum('bhte,hed->btd', o, Wo)
            mem = o[:, :M, :].clone()
            outs.append(o[:, M:, :])
        return torch.concatenate(outs, axis=1)

    def _B_ref(x, w_r, w_gate, w_up, w_down):
        B, S, D = x.shape
        C = 2
        r = x @ w_r
        idx = torch.argsort(-r, axis=-1)[:, :C]
        idx_e = (lambda x, n, axis: torch.repeat_interleave(x, n, dim=axis))(idx.reshape(B, C, 1), D, axis=2)
        x_sel = (lambda x, i, axis: torch.take_along_dim(x, i, dim=axis))(x, idx_e, axis=1)
        g = _silu(x_sel @ w_gate)
        u = x_sel @ w_up
        y = g * u @ w_down
        r_sel = _sigmoid((lambda x, i, axis: torch.take_along_dim(x, i, dim=axis))(r, idx, axis=1))
        y = y * r_sel.reshape(B, C, 1)
        b_off = (torch.arange(B) * S).reshape(B, 1)
        flat_idx = (idx + b_off).reshape(B * C)
        zero = (x * 0.0).reshape(B * S, D)
        upd = _scatter_add(zero, flat_idx, y.reshape(B * C, D), axis=0)
        return x + upd.reshape(B, S, D)
    x = A_x
    mod = (_silu(c) @ w_mod).reshape(c.shape[0], 6, 1, -1)
    sa, ca, ga, sb, cb, gb = (mod[:, 0].clone(), mod[:, 1].clone(), mod[:, 2].clone(), mod[:, 3].clone(), mod[:, 4].clone(), mod[:, 5].clone())
    h = _layernorm(x, axis=-1) * (1 + ca) + sa
    x = x + ga * _A_ref(h, A_mem0, A_Wq, A_Wk, A_Wv, A_Wo, A_seg_len)
    h = _layernorm(x, axis=-1) * (1 + cb) + sb
    x = x + gb * _B_ref(h, B_w_r, B_w_gate, B_w_up, B_w_down)
    return x
```

```cpp
#include <cuda_runtime.h>
#include <cuda_bf16.h>
#include <cuda.h>
#include <stdint.h>

typedef __nv_bfloat16 bf16;

constexpr int S_    = 2048;
constexpr int D_    = 512;
constexpr int H_    = 32;
constexpr int DH_   = 128;
constexpr int HD_   = 4096;
constexpr int M_    = 8;
constexpr int SEG_  = 32;
constexpr int NSEG_ = 64;
constexpr int F_    = 1376;

__device__ __forceinline__ uint32_t smem_u32(const void* p) { return (uint32_t)__cvta_generic_to_shared(p); }
__device__ __forceinline__ uint32_t mapa(uint32_t a, uint32_t r) {
    uint32_t o; asm volatile("mapa.shared::cluster.u32 %0, %1, %2;" : "=r"(o) : "r"(a), "r"(r)); return o;
}
__device__ __forceinline__ void mbar_init(uint32_t b, uint32_t c) {
    asm volatile("mbarrier.init.shared::cta.b64 [%0], %1;" ::"r"(b), "r"(c) : "memory");
}
__device__ __forceinline__ void mbar_expect(uint32_t b, uint32_t bytes) {
    asm volatile("mbarrier.arrive.expect_tx.shared::cta.b64 _, [%0], %1;" ::"r"(b), "r"(bytes) : "memory");
}
__device__ __forceinline__ void mbar_arrive(uint32_t b) {
    asm volatile("mbarrier.arrive.shared::cta.b64 _, [%0];" ::"r"(b) : "memory");
}
__device__ __forceinline__ bool mbar_try(uint32_t b, uint32_t par) {
    uint32_t ok;
    asm volatile("{\n.reg .pred p;\nmbarrier.try_wait.parity.shared::cta.b64 p, [%1], %2;\nselp.u32 %0, 1, 0, p;\n}"
                 : "=r"(ok) : "r"(b), "r"(par) : "memory");
    return ok;
}
__device__ __noinline__ void wait_timeout_trap() { __trap(); }
__device__ __forceinline__ void mbar_wait(uint32_t b, uint32_t par) {
    if (mbar_try(b, par)) return;
    uint32_t n = 0;
    while (!mbar_try(b, par)) { if (++n > (1u << 20)) wait_timeout_trap(); }
}
__device__ __forceinline__ void fence_mbar_init() { asm volatile("fence.mbarrier_init.release.cluster;" ::: "memory"); }
__device__ __forceinline__ void fence_proxy_async() { asm volatile("fence.proxy.async.shared::cta;" ::: "memory"); }
__device__ __forceinline__ void cluster_arrive() { asm volatile("barrier.cluster.arrive.release.aligned;" ::: "memory"); }
__device__ __forceinline__ void cluster_wait() { asm volatile("barrier.cluster.wait.acquire.aligned;" ::: "memory"); }
__device__ __forceinline__ uint32_t cluster_rank() { uint32_t r; asm volatile("mov.u32 %0, %%cluster_ctarank;" : "=r"(r)); return r; }
__device__ __forceinline__ void bar_sync(int id, int n) { asm volatile("bar.sync %0, %1;" ::"r"(id), "r"(n) : "memory"); }
__device__ __forceinline__ void bar_arrive(int id, int n) { asm volatile("bar.arrive %0, %1;" ::"r"(id), "r"(n) : "memory"); }

__device__ __forceinline__ void tma2d(uint32_t dst, const CUtensorMap* tm, int x, int y, uint32_t bar) {
    asm volatile("cp.async.bulk.tensor.2d.shared::cluster.global.mbarrier::complete_tx::bytes [%0], [%1, {%3, %4}], [%2];"
                 ::"r"(dst), "l"(tm), "r"(bar), "r"(x), "r"(y) : "memory");
}
__device__ __forceinline__ void tma2d_store(const CUtensorMap* tm, uint32_t src, int x, int y) {
    asm volatile("cp.async.bulk.tensor.2d.global.shared::cta.bulk_group [%0, {%2, %3}], [%1];"
                 ::"l"(tm), "r"(src), "r"(x), "r"(y) : "memory");
}
__device__ __forceinline__ void tma_prefetch_desc(const CUtensorMap* tm) {
    asm volatile("prefetch.tensormap [%0];" ::"l"(tm) : "memory");
}
__device__ __forceinline__ void bulk_g2s(uint32_t dst, const void* src, uint32_t bytes, uint32_t bar) {
    asm volatile("cp.async.bulk.shared::cluster.global.mbarrier::complete_tx::bytes [%0], [%1], %2, [%3];"
                 ::"r"(dst), "l"(src), "r"(bytes), "r"(bar) : "memory");
}
__device__ __forceinline__ void bulk_s2g(void* dst, uint32_t src, uint32_t bytes) {
    asm volatile("cp.async.bulk.global.shared::cta.bulk_group [%0], [%1], %2;" ::"l"(dst), "r"(src), "r"(bytes) : "memory");
}
__device__ __forceinline__ uint32_t keep(uint32_t x) { uint32_t y; asm volatile("mov.b32 %0, %1;" : "=r"(y) : "r"(x)); return y; }
__device__ __forceinline__ void bulk_commit() { asm volatile("cp.async.bulk.commit_group;" ::: "memory"); }
template <int N> __device__ __forceinline__ void bulk_wait_read() { asm volatile("cp.async.bulk.wait_group.read %0;" ::"n"(N) : "memory"); }
template <int N> __device__ __forceinline__ void bulk_wait() { asm volatile("cp.async.bulk.wait_group %0;" ::"n"(N) : "memory"); }

__device__ __forceinline__ void ldsm4(uint32_t a, uint32_t& r0, uint32_t& r1, uint32_t& r2, uint32_t& r3) {
    asm volatile("ldmatrix.sync.aligned.m8n8.x4.shared.b16 {%0,%1,%2,%3}, [%4];" : "=r"(r0), "=r"(r1), "=r"(r2), "=r"(r3) : "r"(a) : "memory");
}
__device__ __forceinline__ void ldsm4t(uint32_t a, uint32_t& r0, uint32_t& r1, uint32_t& r2, uint32_t& r3) {
    asm volatile("ldmatrix.sync.aligned.m8n8.x4.trans.shared.b16 {%0,%1,%2,%3}, [%4];" : "=r"(r0), "=r"(r1), "=r"(r2), "=r"(r3) : "r"(a) : "memory");
}
__device__ __forceinline__ void stsm2t(uint32_t a, uint32_t r0, uint32_t r1) {
    asm volatile("stmatrix.sync.aligned.m8n8.x2.trans.shared.b16 [%0], {%1,%2};" ::"r"(a), "r"(r0), "r"(r1) : "memory");
}
__device__ __forceinline__ void stsm4(uint32_t a, uint32_t r0, uint32_t r1, uint32_t r2, uint32_t r3) {
    asm volatile("stmatrix.sync.aligned.m8n8.x4.shared.b16 [%0], {%1,%2,%3,%4};" ::"r"(a), "r"(r0), "r"(r1), "r"(r2), "r"(r3) : "memory");
}
__device__ __forceinline__ uint32_t movmat(uint32_t a) {
    uint32_t d; asm volatile("movmatrix.sync.aligned.m8n8.trans.b16 %0, %1;" : "=r"(d) : "r"(a)); return d;
}
__device__ __forceinline__ void mma16816(float* c, uint32_t a0, uint32_t a1, uint32_t a2, uint32_t a3, uint32_t b0, uint32_t b1) {
    asm("mma.sync.aligned.m16n8k16.row.col.f32.bf16.bf16.f32 {%0,%1,%2,%3},{%4,%5,%6,%7},{%8,%9},{%0,%1,%2,%3};"
                 : "+f"(c[0]), "+f"(c[1]), "+f"(c[2]), "+f"(c[3]) : "r"(a0), "r"(a1), "r"(a2), "r"(a3), "r"(b0), "r"(b1));
}
__device__ __forceinline__ void mma1688(float* c, uint32_t a0, uint32_t a1, uint32_t b0) {
    asm("mma.sync.aligned.m16n8k8.row.col.f32.bf16.bf16.f32 {%0,%1,%2,%3},{%4,%5},{%6},{%0,%1,%2,%3};"
                 : "+f"(c[0]), "+f"(c[1]), "+f"(c[2]), "+f"(c[3]) : "r"(a0), "r"(a1), "r"(b0));
}
__device__ __forceinline__ uint32_t pack_bf16(float lo, float hi) {
    uint32_t r; asm("cvt.rn.bf16x2.f32 %0, %1, %2;" : "=r"(r) : "f"(hi), "f"(lo)); return r;
}
__device__ __forceinline__ float bf16r(float x) { return __uint_as_float(pack_bf16(0.f, x) & 0xffff0000u); }
__device__ __forceinline__ float ex2f(float x) { float y; asm("ex2.approx.ftz.f32 %0, %1;" : "=f"(y) : "f"(x)); return y; }
__device__ __forceinline__ float rcpf(float x) { float y; asm("rcp.approx.ftz.f32 %0, %1;" : "=f"(y) : "f"(x)); return y; }
__device__ __forceinline__ float bf_lo(uint32_t w) { return __uint_as_float(w << 16); }
__device__ __forceinline__ float bf_hi(uint32_t w) { return __uint_as_float(w & 0xffff0000u); }

__device__ __forceinline__ void st_async_b32(uint32_t a, uint32_t v, uint32_t mb) {
    asm volatile("st.async.weak.shared::cluster.mbarrier::complete_tx::bytes.b32 [%0], %1, [%2];" ::"r"(a), "r"(v), "r"(mb) : "memory");
}
__device__ __forceinline__ void st_async_v2(uint32_t a, uint32_t v0, uint32_t v1, uint32_t mb) {
    asm volatile("st.async.weak.shared::cluster.mbarrier::complete_tx::bytes.v2.b32 [%0], {%1,%2}, [%3];" ::"r"(a), "r"(v0), "r"(v1), "r"(mb) : "memory");
}
__device__ __forceinline__ void sts32(uint32_t a, uint32_t v) { asm volatile("st.shared.b32 [%0], %1;" ::"r"(a), "r"(v) : "memory"); }
__device__ __forceinline__ void sts128(uint32_t a, float x, float y, float z, float w) {
    asm volatile("st.shared.v4.f32 [%0], {%1,%2,%3,%4};" ::"r"(a), "f"(x), "f"(y), "f"(z), "f"(w) : "memory");
}
__device__ __forceinline__ float lds32f(uint32_t a) { float v; asm volatile("ld.shared.f32 %0, [%1];" : "=f"(v) : "r"(a) : "memory"); return v; }
__device__ __forceinline__ float2 lds64f(uint32_t a) { float2 v; asm volatile("ld.shared.v2.f32 {%0,%1}, [%2];" : "=f"(v.x), "=f"(v.y) : "r"(a) : "memory"); return v; }
__device__ __forceinline__ float4 lds128f(uint32_t a) { float4 v; asm volatile("ld.shared.v4.f32 {%0,%1,%2,%3}, [%4];" : "=f"(v.x), "=f"(v.y), "=f"(v.z), "=f"(v.w) : "r"(a) : "memory"); return v; }

__device__ __forceinline__ uint32_t ld_relaxed_u32(const void* p) {
    uint32_t v; asm volatile("ld.relaxed.gpu.global.b32 %0, [%1];" : "=r"(v) : "l"(p) : "memory"); return v;
}
__device__ __forceinline__ uint32_t ld_acquire_u32(const void* p) {
    uint32_t v; asm volatile("ld.acquire.gpu.global.b32 %0, [%1];" : "=r"(v) : "l"(p) : "memory"); return v;
}
__device__ __forceinline__ void st_relaxed_u32(void* p, uint32_t v) {
    asm volatile("st.relaxed.gpu.global.b32 [%0], %1;" ::"l"(p), "r"(v) : "memory");
}
__device__ __forceinline__ void red_release_add(void* p, uint32_t v) {
    asm volatile("red.release.gpu.global.add.u32 [%0], %1;" ::"l"(p), "r"(v) : "memory");
}
__device__ __forceinline__ uint32_t clock_dep(uint32_t dep) {
    uint32_t t;
    asm volatile("{\n.reg .pred q;\nsetp.ne.u32 q, %1, 0xdeadbeef;\nmov.u32 %0, 0;\n@q mov.u32 %0, %%clock;\n}" : "=r"(t) : "r"(dep) : "memory");
    return t;
}
__device__ __forceinline__ void wait_flag(const uint32_t* p, uint32_t target) {
    uint32_t n = 0;
    while ((int32_t)(ld_acquire_u32(p) - target) < 0) { if (++n > (1u << 22)) wait_timeout_trap(); }
}

__device__ __forceinline__ float silu_f(float x) { return x / (1.f + __expf(-x)); }
__device__ __forceinline__ float warp_sum(float v) {
#pragma unroll
    for (int o = 16; o > 0; o >>= 1) v += __shfl_xor_sync(0xffffffffu, v, o);
    return v;
}
__device__ __forceinline__ void unpack8(const uint4& u, float* f) {
    f[0] = bf_lo(u.x); f[1] = bf_hi(u.x); f[2] = bf_lo(u.y); f[3] = bf_hi(u.y);
    f[4] = bf_lo(u.z); f[5] = bf_hi(u.z); f[6] = bf_lo(u.w); f[7] = bf_hi(u.w);
}

#define TL_MAX(i)
#define TL_MIN(i)
__device__ __forceinline__ void wgmma_ss_n256_tb(float* d, uint64_t da, uint64_t db, int scale_d) {
    asm volatile("{\n.reg .pred p;\nsetp.ne.b32 p, %130, 0;\n"
        "wgmma.mma_async.sync.aligned.m64n256k16.f32.bf16.bf16 "
        "{%0, %1, %2, %3, %4, %5, %6, %7, %8, %9, %10, %11, %12, %13, %14, %15, "
        "%16, %17, %18, %19, %20, %21, %22, %23, %24, %25, %26, %27, %28, %29, %30, %31, "
        "%32, %33, %34, %35, %36, %37, %38, %39, %40, %41, %42, %43, %44, %45, %46, %47, "
        "%48, %49, %50, %51, %52, %53, %54, %55, %56, %57, %58, %59, %60, %61, %62, %63, "
        "%64, %65, %66, %67, %68, %69, %70, %71, %72, %73, %74, %75, %76, %77, %78, %79, "
        "%80, %81, %82, %83, %84, %85, %86, %87, %88, %89, %90, %91, %92, %93, %94, %95, "
        "%96, %97, %98, %99, %100, %101, %102, %103, %104, %105, %106, %107, %108, %109, %110, %111, "
        "%112, %113, %114, %115, %116, %117, %118, %119, %120, %121, %122, %123, %124, %125, %126, %127}, "
        "%128, %129, p, 1, 1, 0, 1;\n}\n"
        : "+f"(d[0]), "+f"(d[1]), "+f"(d[2]), "+f"(d[3]), "+f"(d[4]), "+f"(d[5]), "+f"(d[6]), "+f"(d[7]),
          "+f"(d[8]), "+f"(d[9]), "+f"(d[10]), "+f"(d[11]), "+f"(d[12]), "+f"(d[13]), "+f"(d[14]), "+f"(d[15]),
          "+f"(d[16]), "+f"(d[17]), "+f"(d[18]), "+f"(d[19]), "+f"(d[20]), "+f"(d[21]), "+f"(d[22]), "+f"(d[23]),
          "+f"(d[24]), "+f"(d[25]), "+f"(d[26]), "+f"(d[27]), "+f"(d[28]), "+f"(d[29]), "+f"(d[30]), "+f"(d[31]),
          "+f"(d[32]), "+f"(d[33]), "+f"(d[34]), "+f"(d[35]), "+f"(d[36]), "+f"(d[37]), "+f"(d[38]), "+f"(d[39]),
          "+f"(d[40]), "+f"(d[41]), "+f"(d[42]), "+f"(d[43]), "+f"(d[44]), "+f"(d[45]), "+f"(d[46]), "+f"(d[47]),
          "+f"(d[48]), "+f"(d[49]), "+f"(d[50]), "+f"(d[51]), "+f"(d[52]), "+f"(d[53]), "+f"(d[54]), "+f"(d[55]),
          "+f"(d[56]), "+f"(d[57]), "+f"(d[58]), "+f"(d[59]), "+f"(d[60]), "+f"(d[61]), "+f"(d[62]), "+f"(d[63]),
          "+f"(d[64]), "+f"(d[65]), "+f"(d[66]), "+f"(d[67]), "+f"(d[68]), "+f"(d[69]), "+f"(d[70]), "+f"(d[71]),
          "+f"(d[72]), "+f"(d[73]), "+f"(d[74]), "+f"(d[75]), "+f"(d[76]), "+f"(d[77]), "+f"(d[78]), "+f"(d[79]),
          "+f"(d[80]), "+f"(d[81]), "+f"(d[82]), "+f"(d[83]), "+f"(d[84]), "+f"(d[85]), "+f"(d[86]), "+f"(d[87]),
          "+f"(d[88]), "+f"(d[89]), "+f"(d[90]), "+f"(d[91]), "+f"(d[92]), "+f"(d[93]), "+f"(d[94]), "+f"(d[95]),
          "+f"(d[96]), "+f"(d[97]), "+f"(d[98]), "+f"(d[99]), "+f"(d[100]), "+f"(d[101]), "+f"(d[102]), "+f"(d[103]),
          "+f"(d[104]), "+f"(d[105]), "+f"(d[106]), "+f"(d[107]), "+f"(d[108]), "+f"(d[109]), "+f"(d[110]), "+f"(d[111]),
          "+f"(d[112]), "+f"(d[113]), "+f"(d[114]), "+f"(d[115]), "+f"(d[116]), "+f"(d[117]), "+f"(d[118]), "+f"(d[119]),
          "+f"(d[120]), "+f"(d[121]), "+f"(d[122]), "+f"(d[123]), "+f"(d[124]), "+f"(d[125]), "+f"(d[126]), "+f"(d[127])
        : "l"(da), "l"(db), "r"(scale_d));
}
__device__ __forceinline__ void wgmma_rs_n80(float* d, uint32_t a0, uint32_t a1, uint32_t a2, uint32_t a3, uint64_t db, int scale_d) {
    asm volatile("{\n.reg .pred p;\nsetp.ne.b32 p, %45, 0;\n"
        "wgmma.mma_async.sync.aligned.m64n80k16.f32.bf16.bf16 "
        "{%0, %1, %2, %3, %4, %5, %6, %7, %8, %9, %10, %11, %12, %13, %14, %15, "
        "%16, %17, %18, %19, %20, %21, %22, %23, %24, %25, %26, %27, %28, %29, %30, %31, "
        "%32, %33, %34, %35, %36, %37, %38, %39}, "
        "{%40, %41, %42, %43}, %44, p, 1, 1, 0;\n}\n"
        : "+f"(d[0]), "+f"(d[1]), "+f"(d[2]), "+f"(d[3]), "+f"(d[4]), "+f"(d[5]), "+f"(d[6]), "+f"(d[7]),
          "+f"(d[8]), "+f"(d[9]), "+f"(d[10]), "+f"(d[11]), "+f"(d[12]), "+f"(d[13]), "+f"(d[14]), "+f"(d[15]),
          "+f"(d[16]), "+f"(d[17]), "+f"(d[18]), "+f"(d[19]), "+f"(d[20]), "+f"(d[21]), "+f"(d[22]), "+f"(d[23]),
          "+f"(d[24]), "+f"(d[25]), "+f"(d[26]), "+f"(d[27]), "+f"(d[28]), "+f"(d[29]), "+f"(d[30]), "+f"(d[31]),
          "+f"(d[32]), "+f"(d[33]), "+f"(d[34]), "+f"(d[35]), "+f"(d[36]), "+f"(d[37]), "+f"(d[38]), "+f"(d[39])
        : "r"(a0), "r"(a1), "r"(a2), "r"(a3), "l"(db), "r"(scale_d));
}
__device__ __forceinline__ void wgmma_rs_n64_tb(float* d, uint32_t a0, uint32_t a1, uint32_t a2, uint32_t a3, uint64_t db, int scale_d) {
    asm volatile("{\n.reg .pred p;\nsetp.ne.b32 p, %37, 0;\n"
        "wgmma.mma_async.sync.aligned.m64n64k16.f32.bf16.bf16 "
        "{%0, %1, %2, %3, %4, %5, %6, %7, %8, %9, %10, %11, %12, %13, %14, %15, "
        "%16, %17, %18, %19, %20, %21, %22, %23, %24, %25, %26, %27, %28, %29, %30, %31}, "
        "{%32, %33, %34, %35}, %36, p, 1, 1, 1;\n}\n"
        : "+f"(d[0]), "+f"(d[1]), "+f"(d[2]), "+f"(d[3]), "+f"(d[4]), "+f"(d[5]), "+f"(d[6]), "+f"(d[7]),
          "+f"(d[8]), "+f"(d[9]), "+f"(d[10]), "+f"(d[11]), "+f"(d[12]), "+f"(d[13]), "+f"(d[14]), "+f"(d[15]),
          "+f"(d[16]), "+f"(d[17]), "+f"(d[18]), "+f"(d[19]), "+f"(d[20]), "+f"(d[21]), "+f"(d[22]), "+f"(d[23]),
          "+f"(d[24]), "+f"(d[25]), "+f"(d[26]), "+f"(d[27]), "+f"(d[28]), "+f"(d[29]), "+f"(d[30]), "+f"(d[31])
        : "r"(a0), "r"(a1), "r"(a2), "r"(a3), "l"(db), "r"(scale_d));
}
__device__ __forceinline__ void wgmma_ss_n8_tt(float* d, uint64_t da, uint64_t db, int scale_d) {
    asm volatile("{\n.reg .pred p;\nsetp.ne.b32 p, %6, 0;\n"
        "wgmma.mma_async.sync.aligned.m64n8k16.f32.bf16.bf16 {%0, %1, %2, %3}, %4, %5, p, 1, 1, 1, 1;\n}\n"
        : "+f"(d[0]), "+f"(d[1]), "+f"(d[2]), "+f"(d[3]) : "l"(da), "l"(db), "r"(scale_d));
}
__device__ __forceinline__ void wgmma_fence() { asm volatile("wgmma.fence.sync.aligned;" ::: "memory"); }
__device__ __forceinline__ void wgmma_commit() { asm volatile("wgmma.commit_group.sync.aligned;" ::: "memory"); }
template <int N> __device__ __forceinline__ void wgmma_wait() { asm volatile("wgmma.wait_group.sync.aligned %0;" ::"n"(N) : "memory"); }
template <int N> __device__ __forceinline__ void pin_regs(float* d) {
#pragma unroll
    for (int i = 0; i < N; i++) asm volatile("" : "+f"(d[i])::"memory");
}
__device__ __forceinline__ uint64_t make_desc(uint32_t addr, uint32_t lbo, uint32_t sbo, uint32_t swz) {
    return (uint64_t)((addr & 0x3FFFFu) >> 4) | ((uint64_t)(lbo >> 4) << 16) | ((uint64_t)(sbo >> 4) << 32) | ((uint64_t)swz << 62);
}
__device__ __align__(1024) bf16 g_h[S_ * D_];
__device__ __align__(1024) bf16 g_Kx[S_ * HD_];
__device__ __align__(1024) bf16 g_Vx[S_ * HD_];
__device__ __align__(1024) bf16 g_Km[NSEG_ * M_ * HD_];
__device__ __align__(1024) bf16 g_Vm[NSEG_ * M_ * HD_];
__device__ __align__(8192) uint32_t g_X[2 * 16 * 2 * 4 * 256 + 2048];
__device__ uint32_t g_kvReady[16];
__device__ uint32_t g_memReady[NSEG_];
__device__ __align__(16) float g_mod[6 * D_];
__device__ uint32_t g_modReady[2];
constexpr int MOD_CTAS = 64;
__device__ uint32_t g_epoch;

constexpr int R_THREADS = 256;
constexpr uint32_t R_WV = 0, R_WO = 65536, R_XB = 131072, R_BAR = 196608, R_SMEM = 196608 + 256 + 2048 + 1024;
constexpr uint32_t X_K = R_XB + 0;
constexpr uint32_t X_V = R_XB + 10240;
constexpr uint32_t X_Q = R_XB + 30720;
constexpr uint32_t X_MEMT = R_XB + 31744;
constexpr uint32_t X_RS = R_XB + 39936;
constexpr uint32_t X_OS = R_XB + 48128;
constexpr uint32_t X_VP = R_XB + 50176;
constexpr uint32_t X_LRN = R_XB + 55296;
constexpr uint32_t X_SC = R_XB + 52224;
enum { B_WC0 = 0, B_WC1, B_WC2, B_WC3, B_WC4, B_WC5, B_W2, B_KV0, B_KV1, B_SC, B_VM, B_RS0, B_RS1, B_AG0, B_AG1, B_AG2, B_AG3, B_NUM };
constexpr int KV_JOBS_PER_TILE = 32;
#define AUXREG 24
#define MAINREG 240
#define KEEPALIVE 1
#define XLEARN 12
#define VSPLIT 12
#define POLLGAP 100
#define RS1WAIT 1
#define POLLFIRST 0
#define ABL 0
#define NPOLL 1
#define RS_BF16 1
constexpr uint32_t RS_SRC = RS_BF16 ? 512 : 1024;

struct RParams {
    CUtensorMap tmWq, tmWk, tmWv, tmWo;
    const bf16 *mem0, *c, *w_mod, *x, *wo;
};

#define TR(i, dep)
#define TR0(dep)
#define RP(i)

__global__ void __launch_bounds__(R_THREADS, 1) r_kernel(const __grid_constant__ RParams P) {
    extern __shared__ uint8_t smem_raw[];
    const uint32_t sb = (smem_u32(smem_raw) + 1023u) & ~1023u;
    const int tid = threadIdx.x, lane = tid & 31;
    const int w = __shfl_sync(0xffffffffu, tid >> 5, 0);
    const uint32_t r = cluster_rank();
    const int c = blockIdx.x >> 4;
    const int hl = r >> 1, j = r & 1, h = c * 8 + hl;
    const uint32_t bar0 = sb + R_BAR;
#define BAR(i) (bar0 + 8u * (i))

    if (tid == 0) TL_MIN(0);
    asm volatile("griddepcontrol.launch_dependents;");
    if (tid == 0) {
        const bool rs_self = ((8 * j + 7 >= (int)r) && (8 * j <= (int)r));
        for (int i = 0; i < B_NUM; i++) {
            int cnt = 1;
            if (i == B_SC) cnt += 5;
            if (i == B_VM) cnt += 4;
            if ((i == B_RS0 || i == B_RS1) && rs_self) cnt += 1;
            if (i == B_AG0 || i == B_AG2) cnt += 4;
            mbar_init(BAR(i), cnt);
        }
        fence_mbar_init();
    }
    __syncthreads();
    cluster_arrive();
    cluster_wait();

    const uint32_t ep = ld_relaxed_u32(&g_epoch);
    const int x0 = h * DH_ + 64 * j;
    const bool svc = (tid == 224);
    auto load_w = [&](int q) {
        if (q >= 2) mbar_wait(BAR(B_WC0 + q - 2), 0);
        const CUtensorMap* tm = q < 2 ? &P.tmWk : q < 4 ? &P.tmWv : &P.tmWq;
        const uint32_t dst = sb + (q < 2 ? R_WO : q < 4 ? R_WV : R_XB) + (q & 1) * 32768;
        mbar_expect(BAR(B_WC0 + q), 32768);
        tma2d(dst, tm, x0, (q & 1) * 256, BAR(B_WC0 + q));
    };
    if (w == 7) {
        const char* xp = reinterpret_cast<const char*>(P.x) + (size_t)blockIdx.x * 32768 + lane * 1024;
        asm volatile("cp.async.bulk.prefetch.L2.global [%0], %1;" ::"l"(xp), "r"(1024) : "memory");
        if (lane == 0) { load_w(0); load_w(1); }
        __syncwarp();
    }
    uint32_t wqk[32][4];
    uint32_t wsh[16][4];
    const int mv = w & 3, pv = w >> 2;
    const int l7 = lane & 7, lg = lane >> 3;

    {
        float* red = reinterpret_cast<float*>(smem_raw + (sb - smem_u32(smem_raw)) + R_BAR + 256);
#pragma unroll
        for (int part = 0; part < 2; part++) {
            constexpr int dummy = 0; (void)dummy;
            const int ncg = part ? 4 : 2, nk = part ? 8 : 4;
            const int col0 = part ? 1024 + blockIdx.x * 32 : blockIdx.x * 16;
            const int cg = tid & (ncg - 1), kg = tid / ncg;
            uint4 wv[8];
#pragma unroll
            for (int i = 0; i < 8; i++) if (i < nk) wv[i] = __ldg(reinterpret_cast<const uint4*>(P.w_mod + (size_t)(kg * nk + i) * (6 * D_) + col0 + cg * 8));
            float a8[8] = {0.f, 0.f, 0.f, 0.f, 0.f, 0.f, 0.f, 0.f};
#pragma unroll
            for (int i = 0; i < 8; i++) if (i < nk) {
                const float sv = bf16r(silu_f(__bfloat162float(P.c[kg * nk + i])));
                float f[8]; unpack8(wv[i], f);
#pragma unroll
                for (int e = 0; e < 8; e++) a8[e] = fmaf(sv, f[e], a8[e]);
            }
#pragma unroll
            for (int e = 0; e < 8; e++)
#pragma unroll
                for (int o = 2; o <= 16; o <<= 1) if (o >= ncg) a8[e] += __shfl_xor_sync(0xffffffffu, a8[e], o);
            if (lane < ncg) {
#pragma unroll
                for (int e = 0; e < 8; e++) red[w * 32 + lane * 8 + e] = a8[e];
            }
            bar_sync(3, 256);
            if (tid < ncg * 8) {
                float sm_ = 0.f;
#pragma unroll
                for (int i = 0; i < 8; i++) sm_ += red[i * 32 + tid];
                g_mod[col0 + tid] = bf16r(sm_);
                __syncwarp(ncg == 4 ? 0xffffffffu : 0x0000ffffu);
                if (tid == 0) { red_release_add(&g_modReady[part], 1); if (part == 0) TL_MAX(3); }
            }
            bar_sync(3, 256);
            if (svc) { load_w(2 + 2 * part); load_w(3 + 2 * part); }
            __syncwarp();
        }
    }
    if (w == 7) {
#pragma unroll
        for (int q = 0; q < 4; q++) {
            const char* wp = reinterpret_cast<const char*>(P.wo) + ((size_t)(h * DH_ + q * 32 + lane) * D_ + 256 * j) * 2;
            asm volatile("cp.async.bulk.prefetch.L2.global [%0], %1;" ::"l"(wp), "r"(512) : "memory");
        }
    }
    mbar_wait(BAR(B_WC0), 0); mbar_wait(BAR(B_WC1), 0); mbar_wait(BAR(B_WC4), 0); mbar_wait(BAR(B_WC5), 0);
    {
        const uint32_t base = ((lg & 1) ? (sb + R_WO) : (sb + R_XB)) + ((lg >> 1) * 8 + l7) * 128 + ((w ^ l7) << 4);
#pragma unroll
        for (int cc = 0; cc < 2; cc++)
#pragma unroll
            for (int i = 0; i < 8; i++)
#pragma unroll
                for (int ab = 0; ab < 2; ab++) {
                    const int sg = (r - i - 8 * (ab ^ pv)) & 15;
                    const int idx = (cc * 8 + i) * 2 + ab;
                    ldsm4t(base + (32 * sg + 16 * cc) * 128, wqk[idx][0], wqk[idx][1], wqk[idx][2], wqk[idx][3]);
                }
    }
    bar_sync(1, 256);
    const uint32_t rs_bytes = (((8 * j + 7 >= (int)r) && (8 * j <= (int)r)) ? 7 : 8) * (RS_SRC / 2);
    auto prefetch_kv = [&](int s) {
        if ((s & 3) == 0) wait_flag(&g_kvReady[s >> 2], (ep + 1) * KV_JOBS_PER_TILE);
        asm volatile("fence.proxy.async.global;" ::: "memory");
        const uint32_t b = BAR(B_KV0 + (s & 1));
        const size_t o = (size_t)(s * H_ + h) * 4096;
        mbar_expect(b, 12288);
        bulk_g2s(sb + X_K + (s & 1) * 5120 + 1024, g_Kx + o + j * 2048, 4096, b);
        bulk_g2s(sb + X_V + (s & 1) * 10240 + 1024, g_Vx + o, 4096, b);
        bulk_g2s(sb + X_V + (s & 1) * 10240 + 5120 + 1024, g_Vx + o + 2048, 4096, b);
    };
    if (svc) {
        mbar_expect(BAR(B_W2), 65536);
        for (int b = 0; b < 4; b++) tma2d(sb + R_WO + b * 16384, &P.tmWo, 256 * j + 64 * b, h * DH_, BAR(B_W2));
        mbar_expect(BAR(B_SC), 1280);
        mbar_expect(BAR(B_VM), 1024);
    }
    __syncwarp();
    for (int idx = tid; idx < 4096; idx += 256) {
        const int p = idx >> 8, col = (idx >> 3) & 31, n = idx & 7;
        const int sg = (r - p) & 15;
        const uint16_t v = reinterpret_cast<const uint16_t*>(P.mem0)[n * D_ + 32 * sg + col];
        asm volatile("st.shared.b16 [%0], %1;" ::"r"(sb + X_MEMT + idx * 2), "h"(v) : "memory");
    }
    const uint32_t c_l16 = keep(sb + lane * 16);
    const uint32_t c_l4 = keep(sb + lane * 4);
    const uint32_t c_mb = keep(sb + X_MEMT + ((lane >> 4) ^ pv) * 4096 + (lane & 15) * 16);
    const uint32_t c_st = keep(sb + l7 * 16 + w * 128);
    const uint32_t c_q = keep(sb + X_Q + (lg >> 1) * 128 + l7 * 16);
    const uint32_t c_wv = keep(sb + R_WV + ((lg >> 1) * 8 + l7) * 128 + (((2 * mv + (lg & 1)) ^ l7) << 4));
    const uint32_t c_wo = keep(sb + R_WO + (w >> 1) * 16384 + ((lg >> 1) * 8 + l7) * 128 + (((4 * (w & 1) + (lg & 1)) ^ l7) << 4));
    const uint32_t c_la = keep(sb + X_MEMT + (lane & 1) * 4096 + (4 * w + lg) * 16 + (l7 >> 1) * 4);
    uint32_t* const gx0 = reinterpret_cast<uint32_t*>((reinterpret_cast<uintptr_t>(g_X) + 8191) & ~(uintptr_t)8191) + r * 2048 + tid;
    uint32_t cpsel = 0;
    if (lane < 2) sts32(sb + X_LRN + w * 8 + lane * 4, 0xffffffffu);
    const uint32_t peer = (r ^ 1) << 24;

    auto load_wv_part = [&](int first, int count) {
#pragma unroll
        for (int u = 0; u < count; u++) {
            const int cc = (first + u) >> 3, i = (first + u) & 7;
            const int sg = (r - i - 8 * pv) & 15;
            ldsm4t(c_wv + sg * 4096 + cc * 2048, wsh[cc * 8 + i][0], wsh[cc * 8 + i][1], wsh[cc * 8 + i][2], wsh[cc * 8 + i][3]);
        }
    };
    auto load_wo = [&](int first, int count) {
#pragma unroll
        for (int u = 0; u < count; u++) {
            const int f = first + u;
            ldsm4t((c_wo ^ ((f >> 3) << 5)) + (f & 7) * 2048, wsh[f][0], wsh[f][1], wsh[f][2], wsh[f][3]);
        }
    };
    (void)peer;
    mbar_wait(BAR(B_WC2), 0); mbar_wait(BAR(B_WC3), 0);
    load_wv_part(0, 16);
    mbar_wait(BAR(B_W2), 0);
    bar_sync(3, 256);
    if (tid == 0) TL_MAX(1);
    cluster_arrive();
    cluster_wait();
    if (svc) prefetch_kv(0);
    __syncwarp();

    float aA[4] = {0.f, 0.f, 0.f, 0.f}, aB[4] = {0.f, 0.f, 0.f, 0.f};
    auto zero_mma = [&](float* d) {
        asm volatile("mma.sync.aligned.m16n8k16.row.col.f32.bf16.bf16.f32 {%0,%1,%2,%3},{%4,%5,%6,%7},{%8,%8},{%9,%9,%9,%9};"
                     : "=f"(d[0]), "=f"(d[1]), "=f"(d[2]), "=f"(d[3])
                     : "r"(wqk[0][0]), "r"(wqk[0][1]), "r"(wqk[0][2]), "r"(wqk[0][3]), "r"(0u), "f"(0.f));
    };
    for (int s = 0; s < NSEG_; s++) {
        const uint32_t ph = s & 1;
        const bool full = (s < NSEG_ - 1);
        RP(14);
        float v0[4] = {0.f, 0.f, 0.f, 0.f};
#pragma unroll
        for (int g = 0; g < 8; g++) {
            const int cc = g >> 2;
            if ((g & 1) == 0 && s > 0) mbar_wait(BAR(B_AG0 + (g >> 1)), ph ^ 1);
            if (g == 0) { RP(0); }
            uint32_t bb[2][4];
#pragma unroll
            for (int u = 0; u < 2; u++) ldsm4t(c_mb + ((g & 3) * 2 + u) * 512 + cc * 256, bb[u][0], bb[u][1], bb[u][2], bb[u][3]);
            if (g == 0) TR0(bb[0][0]);
            if (g == 2) TR(1, bb[0][0]);
            if (g == 4) TR(2, bb[0][0]);
            if (g == 6) TR(3, bb[0][0]);
#pragma unroll
            for (int u = 0; u < 2; u++) {
                const int i = (g & 3) * 2 + u;
                const int idx = (cc * 8 + i) * 2;
                mma16816(aA, wqk[idx][0], wqk[idx][1], wqk[idx][2], wqk[idx][3], bb[u][0], bb[u][1]);
                mma16816(aB, wqk[idx + 1][0], wqk[idx + 1][1], wqk[idx + 1][2], wqk[idx + 1][3], bb[u][2], bb[u][3]);
                mma16816(v0, wsh[cc * 8 + i][0], wsh[cc * 8 + i][1], wsh[cc * 8 + i][2], wsh[cc * 8 + i][3], bb[u][0], bb[u][1]);
            }
            if ((g & 1) == 1 && g < 7 && full) load_wo(2 * (g - 1), 4);
        }
        uint32_t kf[8];
        const uint32_t kbuf = c_l16 + X_K + ph * 5120 + w * 1024;
        if (w >= 1 && w <= 4 && full) {
            mbar_wait(BAR(B_KV0 + ph), (s >> 1) & 1);
            ldsm4(kbuf, kf[0], kf[1], kf[2], kf[3]);
            ldsm4(kbuf + 512, kf[4], kf[5], kf[6], kf[7]);
        }
        {
            const uint32_t pq = pack_bf16(aA[0] + aB[0], aA[1] + aB[1]);
            const uint32_t pk = pack_bf16(aA[2] + aB[2], aA[3] + aB[3]);
            TR(4, pq);
            stsm2t(c_st + ((lg & 1) ? X_K + ph * 5120 : X_Q), pq, pk);
        }
        if (pv == 0) sts128(c_l16 + X_VP + mv * 512, v0[0], v0[1], v0[2], v0[3]);
        bar_sync(1, 256);
        const uint32_t c_l8 = 2 * c_l4 - sb;
        if (w <= 4 && full) {
            uint32_t q[4][4];
#pragma unroll
            for (int kk = 0; kk < 4; kk++) ldsm4(c_q + kk * 256, q[kk][0], q[kk][1], q[kk][2], q[kk][3]);
            if (w == 0) {
                ldsm4(kbuf, kf[0], kf[1], kf[2], kf[3]);
                ldsm4(kbuf + 512, kf[4], kf[5], kf[6], kf[7]);
            }
            TR(5, q[0][0]);
            float sc4[4][4];
#pragma unroll
            for (int kk = 0; kk < 4; kk++) {
                sc4[kk][0] = sc4[kk][1] = sc4[kk][2] = sc4[kk][3] = 0.f;
                mma16816(sc4[kk], q[kk][0], q[kk][1], q[kk][2], q[kk][3], kf[2 * kk], kf[2 * kk + 1]);
            }
            const float s0 = (sc4[0][0] + sc4[1][0]) + (sc4[2][0] + sc4[3][0]);
            const float s1 = (sc4[0][1] + sc4[1][1]) + (sc4[2][1] + sc4[3][1]);
            TR(6, __float_as_uint(s0));
            const uint32_t so = c_l8 + X_SC + w * 256;
            st_async_v2(mapa(so + 1280, r ^ 1), __float_as_uint(s0), __float_as_uint(s1), mapa(BAR(B_SC), r ^ 1));
            asm volatile("st.shared.v2.f32 [%0], {%1,%2};" ::"r"(so), "f"(s0), "f"(s1) : "memory");
            __syncwarp();
            if (lane == 0) mbar_arrive(BAR(B_SC));
        }
        if (w >= 4) {
            const float4 p = lds128f(c_l16 + X_VP + mv * 512);
            const uint32_t ta = movmat(pack_bf16(p.x + v0[0], p.y + v0[1]));
            const uint32_t tb = movmat(pack_bf16(p.z + v0[2], p.w + v0[3]));
            const uint32_t oa = c_l4 + X_V + ph * 10240 + j * 5120 + mv * 256;
            const uint32_t rb = mapa(BAR(B_VM), r ^ 1);
            const uint32_t ra = mapa(oa, r ^ 1);
            st_async_b32(ra, ta, rb);
            st_async_b32(ra + 128, tb, rb);
            sts32(oa, ta);
            sts32(oa + 128, tb);
            __syncwarp();
            if (lane == 0) mbar_arrive(BAR(B_VM));
        }
        if (svc) {
            if (full) {
                mbar_expect(BAR(B_RS0), rs_bytes);
                mbar_expect(BAR(B_RS1), rs_bytes);
                mbar_expect(BAR(B_AG0), 2048 - 256);
                mbar_expect(BAR(B_AG1), 2048);
                mbar_expect(BAR(B_AG2), 2048 - 256);
                mbar_expect(BAR(B_AG3), 2048);
            }
            const size_t o = ((size_t)(s * H_ + h) * 2 + j) * 512;
            fence_proxy_async();
            bulk_s2g(g_Km + o, sb + X_K + ph * 5120, 1024);
            if (s + 1 < NSEG_ - 1) prefetch_kv(s + 1);
            mbar_wait(BAR(B_VM), ph);
            fence_proxy_async();
            bulk_s2g(g_Vm + o, sb + X_V + ph * 10240 + j * 5120, 1024);
            bulk_commit();
            if (s > 0) {
                bulk_wait<1>();
                asm volatile("fence.proxy.async.global;" ::: "memory");
                asm volatile("red.relaxed.gpu.global.add.u32 [%0], %1;" ::"l"(&g_memReady[s - 1]), "r"(1u) : "memory");
                TL_MAX(64 + s - 1);
            }
        }
        __syncwarp();
        if (full) {
            load_wo(12, 4);
            if (w < 4) {
                const uint32_t vb0 = sb + X_V + ph * 10240 + (w >> 1) * 5120 + (w & 1) * 512;
                const uint32_t va = keep(vb0 + (lg >> 1) * 1024 + (lg & 1) * 128 + l7 * 16);
                uint32_t v23[2][4], v4[4], v01[2][4];
                const uint32_t sr = keep(c_l8 + X_SC);
                mbar_wait(BAR(B_SC), ph);
                float x[10];
                float2 a[5], b[5];
#pragma unroll
                for (int nt = 0; nt < 5; nt++) { a[nt] = lds64f(sr + nt * 256); b[nt] = lds64f(sr + 1280 + nt * 256); }
                TR(7, __float_as_uint(a[0].x));
#pragma unroll
                for (int nt = 0; nt < 5; nt++) { x[2 * nt] = a[nt].x + b[nt].x; x[2 * nt + 1] = a[nt].y + b[nt].y; }
                pin_regs<10>(x);
#pragma unroll
                for (int u = 0; u < 2; u++) ldsm4t(va + 2048 + u * 256, v23[u][0], v23[u][1], v23[u][2], v23[u][3]);
                ldsm4t(c_l16 - sb + vb0 + 4096, v4[0], v4[1], v4[2], v4[3]);
                float mx = fmaxf(fmaxf(fmaxf(x[0], x[1]), fmaxf(x[2], x[3])), fmaxf(fmaxf(x[4], x[5]), fmaxf(x[6], x[7])));
                mx = fmaxf(mx, fmaxf(x[8], x[9]));
                mx = fmaxf(mx, __shfl_xor_sync(0xffffffffu, mx, 1));
                mx = fmaxf(mx, __shfl_xor_sync(0xffffffffu, mx, 2));
                mbar_wait(BAR(B_VM), ph);
#pragma unroll
                for (int u = 0; u < 2; u++) ldsm4t(va + u * 256, v01[u][0], v01[u][1], v01[u][2], v01[u][3]);
                constexpr float SC = 0.08838834764831845f * 1.4426950408889634f;
                const float mxl = mx * SC;
#pragma unroll
                for (int i = 0; i < 10; i++) x[i] = ex2f(fmaf(x[i], SC, -mxl));
                uint32_t pp[5];
#pragma unroll
                for (int nt = 0; nt < 5; nt++) pp[nt] = pack_bf16(x[2 * nt], x[2 * nt + 1]);
                TR(8, pp[4]);
                float o[2][4], o2[2][4], o3[2][4];
#pragma unroll
                for (int u = 0; u < 2; u++) {
#pragma unroll
                    for (int e = 0; e < 4; e++) o[u][e] = o2[u][e] = o3[u][e] = 0.f;
                    mma16816(o[u], v01[u][0], v01[u][1], v01[u][2], v01[u][3], pp[0], pp[1]);
                    mma16816(o2[u], v23[u][0], v23[u][1], v23[u][2], v23[u][3], pp[2], pp[3]);
                    mma1688(o3[u], v4[2 * u], v4[2 * u + 1], pp[4]);
                }
                float sum = ((x[0] + x[1]) + (x[2] + x[3])) + ((x[4] + x[5]) + (x[6] + x[7])) + (x[8] + x[9]);
                sum += __shfl_xor_sync(0xffffffffu, sum, 1);
                sum += __shfl_xor_sync(0xffffffffu, sum, 2);
                const float inv = rcpf(sum);
                const float ia = __shfl_sync(0xffffffffu, inv, (lane & 3) * 8);
                const float ib = __shfl_sync(0xffffffffu, inv, (lane & 3) * 8 + 4);
                TR(9, __float_as_uint(ib));
#pragma unroll
                for (int u = 0; u < 2; u++) {
                    sts32(c_l4 + X_OS + w * 512 + u * 256, pack_bf16(((o[u][0] + o2[u][0]) + o3[u][0]) * ia, ((o[u][1] + o2[u][1]) + o3[u][1]) * ib));
                    sts32(c_l4 + X_OS + w * 512 + u * 256 + 128, pack_bf16(((o[u][2] + o2[u][2]) + o3[u][2]) * ia, ((o[u][3] + o2[u][3]) + o3[u][3]) * ib));
                }
            }
        }
        const uint32_t dr = 8 * j + w;
        const bool rs_local = (dr == r);
        const uint32_t rsa = keep(mapa(c_l4 + X_RS + hl * RS_SRC, dr));
        bar_sync(2, 256);
        if (!full) break;
        {
            uint32_t ob[16];
#pragma unroll
            for (int qd = 0; qd < 4; qd++) ldsm4t(c_l16 + X_OS + qd * 512, ob[4 * qd], ob[4 * qd + 1], ob[4 * qd + 2], ob[4 * qd + 3]);
            TR(10, ob[0]);
#pragma unroll
            for (int mt = 0; mt < 2; mt++) {
                float a[4] = {0.f, 0.f, 0.f, 0.f}, b[4] = {0.f, 0.f, 0.f, 0.f};
#pragma unroll
                for (int kk = 0; kk < 8; kk += 2) {
                    mma16816(a, wsh[mt * 8 + kk][0], wsh[mt * 8 + kk][1], wsh[mt * 8 + kk][2], wsh[mt * 8 + kk][3], ob[2 * kk], ob[2 * kk + 1]);
                    mma16816(b, wsh[mt * 8 + kk + 1][0], wsh[mt * 8 + kk + 1][1], wsh[mt * 8 + kk + 1][2], wsh[mt * 8 + kk + 1][3], ob[2 * kk + 2], ob[2 * kk + 3]);
                }
                if (mt == 1) TR(11, __float_as_uint(a[0]));
                const uint32_t rb = __byte_perm(BAR(B_RS0 + mt), rsa, 0x7210);
                const uint32_t u0 = pack_bf16(a[0] + b[0], a[1] + b[1]), u1 = pack_bf16(a[2] + b[2], a[3] + b[3]);
                if (rs_local) { sts32(rsa + mt * 256, u0); sts32(rsa + mt * 256 + 128, u1); __syncwarp(); if (lane == 0) mbar_arrive(BAR(B_RS0 + mt)); }
                else { st_async_b32(rsa + mt * 256, u0, rb); st_async_b32(rsa + mt * 256 + 128, u1, rb); }
            }
        }
        if (svc) {
            if (s + 1 < NSEG_ - 1) mbar_expect(BAR(B_SC), 1280);
            mbar_expect(BAR(B_VM), 1024);
        }
        __syncwarp();
        const uint32_t tag = 1u ^ ((s >> 1) & 1);
        const bool learn = s < XLEARN;
        const uint32_t cp = learn ? ((s >> 1) & 1) : ((cpsel >> ph) & 1u);
        uint32_t* gx = gx0 + ph * (16 * 2048) + c * 256;
        uint64_t gxa = reinterpret_cast<uint64_t>(gx);
        uint64_t g1 = (gxa + cp * 4096) ^ 0x400, g2 = (gxa + cp * 4096) ^ 0x800, g3 = (gxa + cp * 4096) ^ 0xc00;
        asm volatile("" : "+l"(gxa), "+l"(g1), "+l"(g2), "+l"(g3));
        const uint32_t rsr = keep(sb + X_RS + (4 * w + lg) * 16 + (l7 >> 1) * 4);
        const uint32_t sel = keep((lane & 1) ? 0x3244u : 0x1044u);
        mbar_wait(BAR(B_RS0 + pv), ph);
        float part;
        {
            float t[8];
#pragma unroll
            for (int src = 0; src < 8; src++) {
                uint32_t u; asm volatile("ld.shared.b32 %0, [%1];" : "=r"(u) : "r"(rsr + src * RS_SRC) : "memory");
                t[src] = __uint_as_float(__byte_perm(u, 0u, sel));
            }
            part = ((t[0] + t[1]) + (t[2] + t[3])) + ((t[4] + t[5]) + (t[6] + t[7]));
        }
        TR(12, __float_as_uint(part));
        const uint32_t mine = (__float_as_uint(part) & ~1u) | tag;
        asm volatile("st.relaxed.gpu.global.b32 [%0], %1;" ::"l"(gxa), "r"(mine) : "memory");
        asm volatile("st.relaxed.gpu.global.b32 [%0+4096], %1;" ::"l"(gxa), "r"(mine) : "memory");
        uint32_t f1, f2, f3;
        auto poll = [&]() {
            asm volatile("ld.relaxed.gpu.global.b32 %0, [%1];" : "=r"(f1) : "l"(g1) : "memory");
            asm volatile("ld.relaxed.gpu.global.b32 %0, [%1];" : "=r"(f2) : "l"(g2) : "memory");
            asm volatile("ld.relaxed.gpu.global.b32 %0, [%1];" : "=r"(f3) : "l"(g3) : "memory");
        };
        uint32_t tl0 = 0;
        if (learn) tl0 = clock_dep(mine);
        poll();
        zero_mma(aA);
        load_wv_part(0, VSPLIT);
        if (learn) {
            const uint32_t rt = clock_dep(f1 ^ f2 ^ f3) - tl0;
            const uint32_t rt0 = __shfl_sync(0xffffffffu, rt, 0);
            uint32_t best; asm volatile("ld.shared.b32 %0, [%1];" : "=r"(best) : "r"(sb + X_LRN + w * 8 + ph * 4) : "memory");
            best = min(best, (rt0 << 1) | cp);
            __syncwarp();
            sts32(sb + X_LRN + w * 8 + ph * 4, best);
            cpsel = (cpsel & ~(1u << ph)) | ((best & 1u) << ph);
        }
        const int ab = lane & 1;
        uint32_t ra[8];
#pragma unroll
        for (int i = 0; i < 8; i++) ra[i] = mapa(c_la + i * 512, (r + i + 8 * ab) & 15);
        const uint32_t agb = keep(BAR(B_AG0 + pv * 2));
        {
            uint32_t n = 0;
            while (true) {
                const uint32_t okm = tag ? (f1 & f2 & f3) : ~(f1 | f2 | f3);
                if (__all_sync(0xffffffffu, okm & 1u)) break;
                poll();
                if (++n > (1u << 21)) wait_timeout_trap();
            }
        }
        TR(13, f1 ^ f2 ^ f3);
        {
            const float tot = (__uint_as_float(mine) + __uint_as_float(f1)) + (__uint_as_float(f2) + __uint_as_float(f3));
            const float y = __shfl_xor_sync(0xffffffffu, tot, 1);
            const uint32_t word = ab ? pack_bf16(y, tot) : pack_bf16(tot, y);
            if (ab) st_async_b32(ra[0], word, __byte_perm(agb, ra[0], 0x7210));
            else sts32(c_la, word);
#pragma unroll
            for (int i = 1; i < 8; i++) st_async_b32(ra[i], word, __byte_perm(agb + 8 * (i >> 2), ra[i], 0x7210));
            __syncwarp();
            if (lane == 0) mbar_arrive(agb);
        }
        load_wv_part(VSPLIT, 16 - VSPLIT);
        zero_mma(aB);
    }
    if (svc) {
        bulk_wait<0>();
        asm volatile("fence.proxy.async.global;" ::: "memory");
        red_release_add(&g_memReady[NSEG_ - 1], 1);
        TL_MAX(64 + NSEG_ - 1);
    }
    st_relaxed_u32(gx0 + 16 * 2048 + c * 256, 1u ^ ((63 >> 1) & 1));
    st_relaxed_u32(gx0 + 16 * 2048 + 1024 + c * 256, 1u ^ ((63 >> 1) & 1));
    cluster_arrive();
    cluster_wait();
#undef BAR
}
__device__ __align__(1024) bf16 g_O[S_ * HD_];
__device__ __align__(1024) float g_part[8 * S_ * D_];
__device__ __align__(1024) float g_part2[8 * 128 * D_];
__device__ __align__(16) bf16 g_x1[S_ * D_];
__device__ __align__(16) bf16 g_h2[S_ * D_];
__device__ __align__(16) float g_r[S_];
__device__ __align__(16) float g_act[2 * F_];
__device__ uint32_t g_hReady[16], g_oReady[16], g_pReady[16], g_ln2Done, g_actReady, g_exitCount, g_jobCounter[2];

constexpr int G_THREADS = 384;
constexpr int G_STAGES = 4;
constexpr uint32_t G_STAGE_BYTES = 49152;
constexpr uint32_t G_BAR = G_STAGES * G_STAGE_BYTES;
constexpr uint32_t G_JOBQ = G_BAR + 192;
constexpr uint32_t G_RED = G_BAR + 256;
constexpr uint32_t G_SMEM = G_RED + 4096 + 1024;
#define WOSPLIT_EARLY 4
#define KV_CTAS 30
enum { JOB_KV = 0, JOB_QA, JOB_WO, JOB_LN2, JOB_END };
constexpr int FFA_CTAS = 43;
constexpr int FFB_CTAS = 32;

struct GParams {
    CUtensorMap tmWq, tmWk, tmWv, tmWo;
    const bf16 *x, *c, *w_mod, *w_r, *w_gate, *w_up, *w_down;
    bf16* out;
};

__device__ __forceinline__ int woSplit(int t) { return t == 15 ? 16 : t >= 13 ? 8 : WOSPLIT_EARLY; }
constexpr int NUM_A = 512;
constexpr int NUM_B = 256 + (13 * 2 * WOSPLIT_EARLY + 2 * 16 + 32) + 256;
__device__ __forceinline__ void decode_job(int g, int& type, int& t, int& a) {
    if (g < NUM_A) { type = JOB_KV; t = g >> 5; a = g & 31; return; }
    g -= NUM_A;
    for (int tt = 0; tt <= 17; tt++) {
        if (tt < 16) { if (g < 16) { type = JOB_QA; t = tt; a = g; return; } g -= 16; }
        if (tt >= 1 && tt <= 16) { const int n = 2 * woSplit(tt - 1); if (g < n) { type = JOB_WO; t = tt - 1; a = g; return; } g -= n; }
        if (tt >= 2) { if (g < 16) { type = JOB_LN2; t = tt - 2; a = g; return; } g -= 16; }
    }
    type = JOB_END; t = 0; a = 0;
}
__device__ __forceinline__ void ln_finish(float sum, float sumsq_centered, float& m, float& den) {
    m = bf16r(sum * (1.f / D_));
    const float v = bf16r(sumsq_centered * (1.f / D_));
    den = bf16r(sqrtf(bf16r(v + 1e-5f)));
}
__device__ __forceinline__ uint32_t ln_apply2(uint32_t x2, uint32_t m2, float rden, uint32_t c2, uint32_t s2) {
    uint32_t d, y, o;
    asm("sub.rn.bf16x2 %0, %1, %2;" : "=r"(d) : "r"(x2), "r"(m2));
    const uint32_t q = pack_bf16(bf_lo(d) * rden, bf_hi(d) * rden);
    asm("mul.rn.bf16x2 %0, %1, %2;" : "=r"(y) : "r"(q), "r"(c2));
    asm("add.rn.bf16x2 %0, %1, %2;" : "=r"(o) : "r"(y), "r"(s2));
    return o;
}
__device__ __forceinline__ float ln_apply(float x, float m, float den, float one_plus_c, float s) {
    const float y = bf16r(bf16r(x - m) * __frcp_rn(den));
    return bf16r(bf16r(y * one_plus_c) + s);
}

__global__ void __launch_bounds__(G_THREADS, 1) g_kernel(const __grid_constant__ GParams P) {
    extern __shared__ uint8_t smem_raw[];
    const uint32_t sb = (smem_u32(smem_raw) + 1023u) & ~1023u;
    const int tid = threadIdx.x, lane = tid & 31;
    const int w = __shfl_sync(0xffffffffu, tid >> 5, 0);
    const int cta = blockIdx.x, nG = gridDim.x;
    const uint32_t fullb = sb + G_BAR, emptyb = sb + G_BAR + 8 * G_STAGES;
    const uint32_t jfull = sb + G_BAR + 64, jempty = sb + G_BAR + 96, jobq = sb + G_JOBQ;
    if (tid == 0) {
        for (int i = 0; i < G_STAGES; i++) { mbar_init(fullb + 8 * i, 1); mbar_init(emptyb + 8 * i, 8); }
        for (int i = 0; i < 4; i++) { mbar_init(jfull + 8 * i, 1); mbar_init(jempty + 8 * i, 9); }
        fence_mbar_init();
    }
    __syncthreads();
    const uint32_t ep = ld_relaxed_u32(&g_epoch);
    const uint32_t ep1 = ep + 1;
    if (tid == 0) TL_MIN(2);

    int jn = 0;
    auto next_job = [&]() {
        const int slot = jn & 3;
        mbar_wait(jfull + 8 * slot, (jn >> 2) & 1);
        int gj; asm volatile("ld.shared.b32 %0, [%1];" : "=r"(gj) : "r"(jobq + 4 * slot) : "memory");
        __syncwarp();
        if (lane == 0) mbar_arrive(jempty + 8 * slot);
        jn++;
        return gj;
    };
    if (w < 4) {
        asm volatile("setmaxnreg.dec.sync.aligned.u32 40;");
        if (w == 1) {
            while (true) {
                int type, t, a;
                decode_job(next_job(), type, t, a);
                if (type == JOB_END) break;
                if (type == JOB_LN2) continue;
                bar_sync(2, 256 + 32);
                if (lane == 0) {
                    uint32_t* f = (type == JOB_KV) ? &g_kvReady[t] : (type == JOB_QA) ? &g_oReady[t] : &g_pReady[t];
                    asm volatile("fence.proxy.async.global;" ::: "memory");
                    red_release_add(f, 1);
                    TL_MAX((type == JOB_KV ? 144 : type == JOB_QA ? 160 : 176) + t);
                }
                __syncwarp();
                bar_arrive(3, 256 + 32);
            }
            return;
        }
        if (w != 0) return;
        int stage = 0; uint32_t phase = 1;
        auto next = [&]() { if (++stage == G_STAGES) { stage = 0; phase ^= 1; } };
        auto acquire_stage = [&](uint32_t bytes) {
            if (lane == 0) { mbar_wait(emptyb + 8 * stage, phase); mbar_expect(fullb + 8 * stage, bytes); }
            __syncwarp();
        };
        auto wait_dep = [&](const uint32_t* f, uint32_t target) {
            if (lane == 0) wait_flag(f, target);
            __syncwarp();
            asm volatile("fence.proxy.async.global;" ::: "memory");
        };
        auto issue_b = [&](int st, const CUtensorMap* tm, int x, int y) {
            if (lane >= 1 && lane <= 4) tma2d(sb + st * G_STAGE_BYTES + 16384 + (lane - 1) * 8192, tm, x + 64 * (lane - 1), y, fullb + 8 * st);
        };
        auto issue_a = [&](int st, const bf16* src) { if (lane == 0) bulk_g2s(sb + st * G_STAGE_BYTES, src, 16384, fullb + 8 * st); };
        auto gemm_stream = [&](const bf16* a0, const CUtensorMap* tm, int x, int y0, int nkb, const uint32_t* dep, uint32_t target) {
            const int pre = nkb < G_STAGES ? nkb : G_STAGES;
            int st0 = stage;
            for (int kb = 0; kb < pre; kb++) { acquire_stage(G_STAGE_BYTES); issue_b(stage, tm, x, y0 + 64 * kb); next(); }
            wait_dep(dep, target);
            for (int kb = 0; kb < pre; kb++) { issue_a(st0, a0 + (size_t)kb * 8192); if (++st0 == G_STAGES) st0 = 0; }
            for (int kb = pre; kb < nkb; kb++) {
                acquire_stage(G_STAGE_BYTES);
                issue_a(stage, a0 + (size_t)kb * 8192);
                issue_b(stage, tm, x, y0 + 64 * kb);
                next();
            }
        };
        bool inA = true;
        for (int pn = 0;; pn++) {
            const int slot = pn & 3;
            int g = NUM_A;
            if (lane == 0) {
                mbar_wait(jempty + 8 * slot, ((pn >> 2) & 1) ^ 1);
                if (inA) {
                    g = (int)atomicAdd(&g_jobCounter[0], 1u);
                    if (g >= NUM_A) { inA = false; g = NUM_A; }
                    else if (cta >= KV_CTAS) inA = false;
                }
                if (g >= NUM_A) g = NUM_A + (int)atomicAdd(&g_jobCounter[1], 1u);
                sts32(jobq + 4 * slot, (uint32_t)g);
                mbar_arrive(jfull + 8 * slot);
            }
            g = __shfl_sync(0xffffffffu, g, 0);
            int type, t, a;
            decode_job(g, type, t, a);
            if (type == JOB_END) break;
            if (lane == 0) { if (type == JOB_QA) TL_MAX(208 + t); if (type == JOB_WO) TL_MAX(240 + t); if (type == JOB_LN2) TL_MAX(256 + t); }
            if (type == JOB_KV || type == JOB_QA) {
                const CUtensorMap* tm = (type == JOB_QA) ? &P.tmWq : (a < 16 ? &P.tmWk : &P.tmWv);
                gemm_stream(g_h + (size_t)t * 8 * 8192, tm, (a & 15) * 256, 0, 8, &g_hReady[t], ep1 * 16);
                if (type == JOB_QA) {
                    const int cwg = (lane >> 3) & 1, j = (lane >> 2) & 1, piece = lane & 3;
                    wait_dep(&g_kvReady[t], ep1 * KV_JOBS_PER_TILE);
                    int st0 = stage;
                    for (int q = 0; q < 4; q++) {
                        acquire_stage(40960);
                        if (lane < 16 && piece < 2) {
                            const size_t oa = ((size_t)(4 * t + 2 * cwg + piece) * H_ + 2 * a + (q >> 1)) * 2 + j;
                            bulk_g2s(sb + stage * G_STAGE_BYTES + cwg * 20480 + j * 10240 + piece * 4096, ((q & 1) ? g_Vx : g_Kx) + oa * 2048, 4096, fullb + 8 * stage);
                        }
                        next();
                    }
                    wait_dep(&g_memReady[4 * t + 3], ep1 * 64);
                    for (int q = 0; q < 4; q++) {
                        if (lane < 16 && piece >= 2) {
                            const size_t oa = ((size_t)(4 * t + 2 * cwg + piece - 2) * H_ + 2 * a + (q >> 1)) * 2 + j;
                            bulk_g2s(sb + st0 * G_STAGE_BYTES + cwg * 20480 + j * 10240 + 8192 + (piece - 2) * 1024, ((q & 1) ? g_Vm : g_Km) + oa * 512, 1024, fullb + 8 * st0);
                        }
                        if (++st0 == G_STAGES) st0 = 0;
                    }
                }
            } else if (type == JOB_WO) {
                const int nkb = 64 / woSplit(t), kb0 = (a >> 1) * nkb;
                gemm_stream(g_O + (size_t)(t * 64 + kb0) * 8192, &P.tmWo, (a & 1) * 256, 64 * kb0, nkb, &g_oReady[t], ep1 * 16);
            } else {
                if (lane == 0) wait_flag(&g_pReady[t], ep1 * 2 * woSplit(t));
                __syncwarp();
            }
        }
        return;
    }

    asm volatile("setmaxnreg.inc.sync.aligned.u32 232;");
    const int ct = tid - 128;
    const int cw = w - 4;
    const int wg = cw >> 2, wq = cw & 3;
    const int qn = lane >> 2, qt = lane & 3;
    float* red = reinterpret_cast<float*>(smem_raw + (sb - smem_u32(smem_raw)) + G_RED);

    {
        uint32_t* sS = reinterpret_cast<uint32_t*>(red);
        uint32_t* sC = reinterpret_cast<uint32_t*>(red) + 256;
        const int rbg = cta + nG * cw;
        const bool doln = rbg < 256;
        const int row = (doln ? rbg : 0) * 8 + (lane & 7), part = lane >> 3;
        uint4 xv[16];
        if (doln) {
#pragma unroll
            for (int i = 0; i < 16; i++) xv[i] = __ldg(reinterpret_cast<const uint4*>(P.x + (size_t)row * D_ + part * 128 + i * 8));
        }
        float m = 0.f, den = 1.f;
        if (doln) {
            float sum = 0.f;
#pragma unroll
            for (int i = 0; i < 16; i++) { float f[8]; unpack8(xv[i], f); for (int e = 0; e < 8; e++) sum += f[e]; }
            sum += __shfl_xor_sync(0xffffffffu, sum, 8); sum += __shfl_xor_sync(0xffffffffu, sum, 16);
            const float mean = sum * (1.f / D_);
            float sq = 0.f;
#pragma unroll
            for (int i = 0; i < 16; i++) { float f[8]; unpack8(xv[i], f); for (int e = 0; e < 8; e++) sq = fmaf(f[e] - mean, f[e] - mean, sq); }
            sq += __shfl_xor_sync(0xffffffffu, sq, 8); sq += __shfl_xor_sync(0xffffffffu, sq, 16);
            ln_finish(sum, sq, m, den);
        }
        if (ct == 0) wait_flag(&g_modReady[0], ep1 * MOD_CTAS);
        bar_sync(1, 256);
        {
            const float2 sv = __ldcg(reinterpret_cast<const float2*>(g_mod + 2 * ct)), cv = __ldcg(reinterpret_cast<const float2*>(g_mod + D_ + 2 * ct));
            sS[ct] = pack_bf16(sv.x, sv.y);
            sC[ct] = pack_bf16(1.f + cv.x, 1.f + cv.y);
        }
        bar_sync(1, 256);
        if (doln) {
            const int t = rbg >> 4, rb = rbg & 15;
            const float rden = __frcp_rn(den);
            const uint32_t m2 = pack_bf16(m, m);
#pragma unroll
            for (int i = 0; i < 16; i++) {
                const int col = part * 128 + i * 8;
                const uint4 s4 = *reinterpret_cast<const uint4*>(sS + col / 2), c4 = *reinterpret_cast<const uint4*>(sC + col / 2);
                uint4 o;
                o.x = ln_apply2(xv[i].x, m2, rden, c4.x, s4.x);
                o.y = ln_apply2(xv[i].y, m2, rden, c4.y, s4.y);
                o.z = ln_apply2(xv[i].z, m2, rden, c4.z, s4.z);
                o.w = ln_apply2(xv[i].w, m2, rden, c4.w, s4.w);
                const int kb = col >> 6, kc = (col >> 3) & 7;
                *reinterpret_cast<uint4*>(g_h + ((((size_t)(t * 8 + kb) * 16 + rb) * 8 + kc) * 8 + (lane & 7)) * 8) = o;
            }
            asm volatile("fence.proxy.async.global;" ::: "memory");
            __syncwarp();
            if (lane == 0) { red_release_add(&g_hReady[t], 1); TL_MAX(128 + t); }
        }
        bar_sync(1, 256);
    }

    int stage = 0; uint32_t phase = 0;
    auto next = [&]() { if (++stage == G_STAGES) { stage = 0; phase ^= 1; } };
    bool first_job = true;
    auto job_done = [&]() {
        if (!first_job) bar_sync(3, 256 + 32);
        first_job = false;
        bar_arrive(2, 256 + 32);
    };
    auto release = [&](int st) { __syncwarp(); if (lane == 0) mbar_arrive(emptyb + 8 * st); };
    while (true) {
        int type, t, a;
        decode_job(next_job(), type, t, a);
        if (type == JOB_END) break;
        if (type == JOB_LN2) {
            const int row = t * 128 + a * 8 + cw;
            const int ns = woSplit(t);
            if (lane == 0) { wait_flag(&g_modReady[1], ep1 * MOD_CTAS); wait_flag(&g_pReady[t], ep1 * 2 * ns); }
            __syncwarp();
            float x1[16], h2[16];
            float sum = 0.f;
            {
                float4 s[4];
#pragma unroll
                for (int i = 0; i < 4; i++) s[i] = make_float4(0.f, 0.f, 0.f, 0.f);
                const float* p0 = g_part + (size_t)row * D_ + 4 * lane;
                for (int k0 = 0; k0 < ns; k0 += 4) {
                    float4 v[4][4];
#pragma unroll
                    for (int k = 0; k < 4; k++) {
                        const int kk = k0 + k;
                        const float* p = kk < 8 ? p0 + (size_t)kk * S_ * D_ : g_part2 + ((size_t)(kk - 8) * 128 + (row & 127)) * D_ + 4 * lane;
#pragma unroll
                        for (int i = 0; i < 4; i++) v[k][i] = __ldcg(reinterpret_cast<const float4*>(p + 128 * i));
                    }
#pragma unroll
                    for (int k = 0; k < 4; k++)
#pragma unroll
                        for (int i = 0; i < 4; i++) { s[i].x += v[k][i].x; s[i].y += v[k][i].y; s[i].z += v[k][i].z; s[i].w += v[k][i].w; }
                }
#pragma unroll
                for (int i = 0; i < 4; i++) {
                    const int col = 128 * i + 4 * lane;
                    const uint2 xu = __ldg(reinterpret_cast<const uint2*>(P.x + (size_t)row * D_ + col));
                    const float4 ga = __ldcg(reinterpret_cast<const float4*>(g_mod + 2 * D_ + col));
                    x1[4 * i + 0] = bf16r(bf_lo(xu.x) + bf16r(ga.x * bf16r(s[i].x)));
                    x1[4 * i + 1] = bf16r(bf_hi(xu.x) + bf16r(ga.y * bf16r(s[i].y)));
                    x1[4 * i + 2] = bf16r(bf_lo(xu.y) + bf16r(ga.z * bf16r(s[i].z)));
                    x1[4 * i + 3] = bf16r(bf_hi(xu.y) + bf16r(ga.w * bf16r(s[i].w)));
                    sum += (x1[4 * i] + x1[4 * i + 1]) + (x1[4 * i + 2] + x1[4 * i + 3]);
                }
            }
            sum = warp_sum(sum);
            const float mean = sum * (1.f / D_);
            float sq = 0.f;
#pragma unroll
            for (int e = 0; e < 16; e++) sq = fmaf(x1[e] - mean, x1[e] - mean, sq);
            sq = warp_sum(sq);
            float m, den; ln_finish(sum, sq, m, den);
            float rr = 0.f;
#pragma unroll
            for (int i = 0; i < 4; i++) {
                const int col = 128 * i + 4 * lane;
                const float4 sbv = __ldcg(reinterpret_cast<const float4*>(g_mod + 3 * D_ + col));
                const float4 cbv = __ldcg(reinterpret_cast<const float4*>(g_mod + 4 * D_ + col));
                const float4 gbv = __ldcg(reinterpret_cast<const float4*>(g_mod + 5 * D_ + col));
                const uint2 wu = __ldg(reinterpret_cast<const uint2*>(P.w_r + col));
                h2[4 * i + 0] = ln_apply(x1[4 * i + 0], m, den, bf16r(1.f + cbv.x), sbv.x);
                h2[4 * i + 1] = ln_apply(x1[4 * i + 1], m, den, bf16r(1.f + cbv.y), sbv.y);
                h2[4 * i + 2] = ln_apply(x1[4 * i + 2], m, den, bf16r(1.f + cbv.z), sbv.z);
                h2[4 * i + 3] = ln_apply(x1[4 * i + 3], m, den, bf16r(1.f + cbv.w), sbv.w);
                rr = fmaf(h2[4 * i + 0], bf_lo(wu.x), rr); rr = fmaf(h2[4 * i + 1], bf_hi(wu.x), rr);
                rr = fmaf(h2[4 * i + 2], bf_lo(wu.y), rr); rr = fmaf(h2[4 * i + 3], bf_hi(wu.y), rr);
                uint2 o, u1, u2;
                o.x = pack_bf16(x1[4 * i + 0] + bf16r(gbv.x * h2[4 * i + 0]), x1[4 * i + 1] + bf16r(gbv.y * h2[4 * i + 1]));
                o.y = pack_bf16(x1[4 * i + 2] + bf16r(gbv.z * h2[4 * i + 2]), x1[4 * i + 3] + bf16r(gbv.w * h2[4 * i + 3]));
                u1.x = pack_bf16(x1[4 * i + 0], x1[4 * i + 1]); u1.y = pack_bf16(x1[4 * i + 2], x1[4 * i + 3]);
                u2.x = pack_bf16(h2[4 * i + 0], h2[4 * i + 1]); u2.y = pack_bf16(h2[4 * i + 2], h2[4 * i + 3]);
                *reinterpret_cast<uint2*>(P.out + (size_t)row * D_ + col) = o;
                *reinterpret_cast<uint2*>(g_x1 + (size_t)row * D_ + col) = u1;
                *reinterpret_cast<uint2*>(g_h2 + (size_t)row * D_ + col) = u2;
            }
            rr = warp_sum(rr);
            if (lane == 0) g_r[row] = bf16r(rr);
            __syncwarp();
            if (lane == 0) { red_release_add(&g_ln2Done, 1); TL_MAX(192 + t); }
            continue;
        }
        float acc[128];
        const int nkb = (type == JOB_WO) ? 64 / woSplit(t) : 8;
        {
            int prev = -1;
            for (int kb = 0; kb < nkb; kb++) {
                mbar_wait(fullb + 8 * stage, phase);
                const uint32_t st = sb + stage * G_STAGE_BYTES;
                const uint64_t da = make_desc(st + wg * 8192, 128, 1024, 0);
                const uint64_t db = make_desc(st + 16384, 8192, 1024, 1);
                wgmma_fence();
#pragma unroll
                for (int kk = 0; kk < 4; kk++) wgmma_ss_n256_tb(acc, da + kk * 16, db + kk * 128, (kb | kk) != 0);
                wgmma_commit();
                if (prev >= 0) { wgmma_wait<1>(); release(prev); }
                prev = stage;
                next();
            }
            wgmma_wait<0>();
            pin_regs<128>(acc);
            release(prev);
        }
        if (type == JOB_KV) {
            bf16* dst = (a < 16) ? g_Kx : g_Vx;
            const int seg = 4 * t + 2 * wg + (wq >> 1), tb = 2 * (wq & 1);
#pragma unroll
            for (int i = 0; i < 32; i++) {
                const int head = 2 * (a & 15) + (i >> 4), j = (i >> 3) & 1, ec = i & 7;
                uint32_t* p = reinterpret_cast<uint32_t*>(dst + ((((size_t)(seg * H_ + head) * 2 + j) * 4 + tb) * 8 + ec) * 64) + lane;
                p[0] = pack_bf16(acc[4 * i], acc[4 * i + 1]);
                p[256] = pack_bf16(acc[4 * i + 2], acc[4 * i + 3]);
            }
            job_done();
        } else if (type == JOB_WO) {
            const int kc = a >> 1;
            float* dst = (kc < 8 ? g_part + ((size_t)kc * S_ + t * 128) * D_ : g_part2 + (size_t)(kc - 8) * 128 * D_) + (size_t)(wg * 64 + wq * 16 + qn) * D_ + (a & 1) * 256 + 2 * qt;
#pragma unroll
            for (int i = 0; i < 32; i++) {
                *reinterpret_cast<float2*>(dst + 8 * i) = make_float2(acc[4 * i], acc[4 * i + 1]);
                *reinterpret_cast<float2*>(dst + 8 * D_ + 8 * i) = make_float2(acc[4 * i + 2], acc[4 * i + 3]);
            }
            job_done();
        } else {
            if (ct == 0) TL_MAX(224 + t);
            uint32_t qa[2][8][4];
#pragma unroll
            for (int hd = 0; hd < 2; hd++)
#pragma unroll
                for (int kk = 0; kk < 8; kk++) {
                    const int i0 = 16 * hd + 2 * kk;
                    qa[hd][kk][0] = pack_bf16(acc[4 * i0], acc[4 * i0 + 1]);
                    qa[hd][kk][1] = pack_bf16(acc[4 * i0 + 2], acc[4 * i0 + 3]);
                    qa[hd][kk][2] = pack_bf16(acc[4 * i0 + 4], acc[4 * i0 + 5]);
                    qa[hd][kk][3] = pack_bf16(acc[4 * i0 + 6], acc[4 * i0 + 7]);
                }
            const bool segB = wq >= 2;
            const int rho0 = 16 * (wq & 1) + qn;
#pragma unroll
            for (int hd = 0; hd < 2; hd++) {
                float sc[40];
                mbar_wait(fullb + 8 * stage, phase);
                {
                    const uint32_t kb = sb + stage * G_STAGE_BYTES + wg * 20480;
                    wgmma_fence();
#pragma unroll
                    for (int kk = 0; kk < 8; kk++)
                        wgmma_rs_n80(sc, qa[hd][kk][0], qa[hd][kk][1], qa[hd][kk][2], qa[hd][kk][3],
                                     make_desc(kb + (kk >> 2) * 10240 + (kk & 3) * 256, 128, 1024, 0), kk != 0);
                    wgmma_commit();
                    wgmma_wait<0>();
                    pin_regs<40>(sc);
                    release(stage);
                    next();
                }
                if (ct == 0 && hd == 0) TL_MAX(272 + t);
                float x[2][10];
#pragma unroll
                for (int nt = 0; nt < 5; nt++) {
                    const int bA = (nt < 4) ? nt : 8, bB = (nt < 4) ? 4 + nt : 9;
#pragma unroll
                    for (int e = 0; e < 2; e++) {
                        float v0 = segB ? sc[4 * bB + e] : sc[4 * bA + e];
                        float v1 = segB ? sc[4 * bB + 2 + e] : sc[4 * bA + 2 + e];
                        v0 = bf16r(bf16r(v0) * 0.08838834764831845f);
                        v1 = bf16r(bf16r(v1) * 0.08838834764831845f);
                        if (nt < 4) {
                            const int kappa = 8 * nt + 2 * qt + e;
                            if (kappa > rho0) v0 = -1e9f;
                            if (kappa > rho0 + 8) v1 = -1e9f;
                        }
                        x[0][2 * nt + e] = v0;
                        x[1][2 * nt + e] = v1;
                    }
                }
                uint32_t pp[2][5];
#pragma unroll
                for (int rr = 0; rr < 2; rr++) {
                    float mx = x[rr][0];
#pragma unroll
                    for (int i = 1; i < 10; i++) mx = fmaxf(mx, x[rr][i]);
                    mx = fmaxf(mx, __shfl_xor_sync(0xffffffffu, mx, 1));
                    mx = fmaxf(mx, __shfl_xor_sync(0xffffffffu, mx, 2));
                    float sum = 0.f;
#pragma unroll
                    for (int i = 0; i < 10; i++) { x[rr][i] = ex2f((x[rr][i] - mx) * 1.4426950408889634f); sum += x[rr][i]; }
                    sum += __shfl_xor_sync(0xffffffffu, sum, 1);
                    sum += __shfl_xor_sync(0xffffffffu, sum, 2);
                    const float inv = __fdiv_rn(1.f, sum);
#pragma unroll
                    for (int nt = 0; nt < 5; nt++) pp[rr][nt] = pack_bf16(x[rr][2 * nt] * inv, x[rr][2 * nt + 1] * inv);
                }
                uint32_t pa[5][4];
#pragma unroll
                for (int u = 0; u < 2; u++) {
#pragma unroll
                    for (int q = 0; q < 4; q++) {
                        const uint32_t v = pp[q & 1][2 * u + (q >> 1)];
                        pa[u][q] = segB ? 0u : v;
                        pa[2 + u][q] = segB ? v : 0u;
                    }
                }
                pa[4][0] = segB ? 0u : pp[0][4]; pa[4][1] = segB ? 0u : pp[1][4];
                pa[4][2] = segB ? pp[0][4] : 0u; pa[4][3] = segB ? pp[1][4] : 0u;
                float o[64];
                mbar_wait(fullb + 8 * stage, phase);
                {
                    const uint32_t vb = sb + stage * G_STAGE_BYTES + wg * 20480;
                    wgmma_fence();
#pragma unroll
                    for (int j = 0; j < 2; j++)
#pragma unroll
                        for (int u = 0; u < 5; u++)
                            wgmma_rs_n64_tb(o + 32 * j, pa[u][0], pa[u][1], pa[u][2], pa[u][3],
                                            make_desc(vb + j * 10240 + u * 2048, 1024, 128, 0), u != 0);
                    wgmma_commit();
                    wgmma_wait<0>();
                    pin_regs<64>(o);
                    release(stage);
                    next();
                }
                const int head = 2 * a + hd, rb = 8 * wg + 2 * wq;
#pragma unroll
                for (int j = 0; j < 2; j++)
#pragma unroll
                    for (int ec = 0; ec < 8; ec++) {
                        uint32_t* p = reinterpret_cast<uint32_t*>(g_O + ((((size_t)(t * 64 + 2 * head + j) * 16 + rb) * 8 + ec) * 64)) + lane;
                        p[0] = pack_bf16(o[32 * j + 4 * ec], o[32 * j + 4 * ec + 1]);
                        p[256] = pack_bf16(o[32 * j + 4 * ec + 2], o[32 * j + 4 * ec + 3]);
                    }
            }
            if (ct == 0) TL_MAX(288 + t);
            job_done();
        }
    }

    if (cta < FFA_CTAS) {
        const int cg = ct & 3, kg = ct >> 2;
        uint4 wg_[8], wu_[8];
#pragma unroll
        for (int i = 0; i < 8; i++) {
            wg_[i] = __ldg(reinterpret_cast<const uint4*>(P.w_gate + (size_t)(kg * 8 + i) * F_ + cta * 32 + cg * 8));
            wu_[i] = __ldg(reinterpret_cast<const uint4*>(P.w_up + (size_t)(kg * 8 + i) * F_ + cta * 32 + cg * 8));
        }
        uint4 wd_[11];
        const int dcg = ct & 1, dkg = ct >> 1;
        if (cta < FFB_CTAS) {
#pragma unroll
            for (int i = 0; i < 11; i++) {
                const int k = dkg + 128 * i;
                wd_[i] = (k < F_) ? __ldg(reinterpret_cast<const uint4*>(P.w_down + (size_t)k * D_ + cta * 16 + dcg * 8)) : make_uint4(0, 0, 0, 0);
            }
        }
        if (ct == 0) wait_flag(&g_ln2Done, ep1 * S_);
        bar_sync(1, 256);
        float b1 = -INFINITY, b2 = -INFINITY; int i1 = 0x7fffffff, i2 = 0x7fffffff;
        auto better = [](float v, int i, float bv, int bi) { return v > bv || (v == bv && i < bi); };
        auto insert = [&](float v, int i) {
            if (better(v, i, b1, i1)) { b2 = b1; i2 = i1; b1 = v; i1 = i; }
            else if (better(v, i, b2, i2)) { b2 = v; i2 = i; }
        };
#pragma unroll
        for (int i = 0; i < 8; i++) insert(__ldcg(g_r + ct + 256 * i), ct + 256 * i);
#pragma unroll
        for (int o = 16; o > 0; o >>= 1) {
            const float v1 = __shfl_xor_sync(0xffffffffu, b1, o), v2 = __shfl_xor_sync(0xffffffffu, b2, o);
            const int j1 = __shfl_xor_sync(0xffffffffu, i1, o), j2 = __shfl_xor_sync(0xffffffffu, i2, o);
            insert(v1, j1); insert(v2, j2);
        }
        int* redi = reinterpret_cast<int*>(red);
        if (lane == 0) { red[cw * 4] = b1; redi[cw * 4 + 1] = i1; red[cw * 4 + 2] = b2; redi[cw * 4 + 3] = i2; }
        bar_sync(1, 256);
        b1 = b2 = -INFINITY; i1 = i2 = 0x7fffffff;
#pragma unroll
        for (int i = 0; i < 8; i++) { insert(red[i * 4], redi[i * 4 + 1]); insert(red[i * 4 + 2], redi[i * 4 + 3]); }
        bar_sync(1, 256);
        float ga0[8], ga1[8], ua0[8], ua1[8];
#pragma unroll
        for (int e = 0; e < 8; e++) ga0[e] = ga1[e] = ua0[e] = ua1[e] = 0.f;
        {
            const uint4 xa = __ldcg(reinterpret_cast<const uint4*>(g_h2 + (size_t)i1 * D_ + kg * 8));
            const uint4 xb = __ldcg(reinterpret_cast<const uint4*>(g_h2 + (size_t)i2 * D_ + kg * 8));
            float fa[8], fb[8]; unpack8(xa, fa); unpack8(xb, fb);
#pragma unroll
            for (int i = 0; i < 8; i++) {
                float g8[8], u8[8]; unpack8(wg_[i], g8); unpack8(wu_[i], u8);
#pragma unroll
                for (int e = 0; e < 8; e++) {
                    ga0[e] = fmaf(fa[i], g8[e], ga0[e]); ga1[e] = fmaf(fb[i], g8[e], ga1[e]);
                    ua0[e] = fmaf(fa[i], u8[e], ua0[e]); ua1[e] = fmaf(fb[i], u8[e], ua1[e]);
                }
            }
        }
#pragma unroll
        for (int e = 0; e < 8; e++)
#pragma unroll
            for (int o = 4; o <= 16; o <<= 1) {
                ga0[e] += __shfl_xor_sync(0xffffffffu, ga0[e], o); ga1[e] += __shfl_xor_sync(0xffffffffu, ga1[e], o);
                ua0[e] += __shfl_xor_sync(0xffffffffu, ua0[e], o); ua1[e] += __shfl_xor_sync(0xffffffffu, ua1[e], o);
            }
        if (lane < 4) {
#pragma unroll
            for (int e = 0; e < 8; e++) {
                red[(cw * 4 + 0) * 32 + lane * 8 + e] = ga0[e]; red[(cw * 4 + 1) * 32 + lane * 8 + e] = ga1[e];
                red[(cw * 4 + 2) * 32 + lane * 8 + e] = ua0[e]; red[(cw * 4 + 3) * 32 + lane * 8 + e] = ua1[e];
            }
        }
        bar_sync(1, 256);
        if (ct < 64) {
            const int tok = ct >> 5, col = ct & 31;
            float gs = 0.f, us = 0.f;
#pragma unroll
            for (int i = 0; i < 8; i++) { gs += red[(i * 4 + tok) * 32 + col]; us += red[(i * 4 + 2 + tok) * 32 + col]; }
            const float gv = bf16r(silu_f(bf16r(gs)));
            g_act[tok * F_ + cta * 32 + col] = bf16r(gv * bf16r(us));
        }
        bar_sync(1, 256);
        if (ct == 0) { red_release_add(&g_actReady, 1); TL_MAX(4); }
        if (cta < FFB_CTAS) {
            if (ct == 0) wait_flag(&g_actReady, ep1 * FFA_CTAS);
            bar_sync(1, 256);
            float y0[8], y1[8];
#pragma unroll
            for (int e = 0; e < 8; e++) y0[e] = y1[e] = 0.f;
#pragma unroll
            for (int i = 0; i < 11; i++) {
                const int k = dkg + 128 * i;
                const float a0 = (k < F_) ? __ldcg(g_act + k) : 0.f, a1 = (k < F_) ? __ldcg(g_act + F_ + k) : 0.f;
                float d8[8]; unpack8(wd_[i], d8);
#pragma unroll
                for (int e = 0; e < 8; e++) { y0[e] = fmaf(a0, d8[e], y0[e]); y1[e] = fmaf(a1, d8[e], y1[e]); }
            }
#pragma unroll
            for (int e = 0; e < 8; e++)
#pragma unroll
                for (int o = 2; o <= 16; o <<= 1) { y0[e] += __shfl_xor_sync(0xffffffffu, y0[e], o); y1[e] += __shfl_xor_sync(0xffffffffu, y1[e], o); }
            if (lane < 2) {
#pragma unroll
                for (int e = 0; e < 8; e++) { red[(cw * 2 + 0) * 16 + lane * 8 + e] = y0[e]; red[(cw * 2 + 1) * 16 + lane * 8 + e] = y1[e]; }
            }
            bar_sync(1, 256);
            if (ct < 32) {
                const int tok = ct >> 4, cl = ct & 15, col = cta * 16 + cl;
                float ys = 0.f;
#pragma unroll
                for (int i = 0; i < 8; i++) ys += red[(i * 2 + tok) * 16 + cl];
                const int row = tok ? i2 : i1;
                const float rv = tok ? b2 : b1;
                const float sg = bf16r(1.f / (1.f + __expf(-rv)));
                const float upd = bf16r(bf16r(ys) * sg);
                const uint16_t* x1p = reinterpret_cast<const uint16_t*>(g_x1), *h2p = reinterpret_cast<const uint16_t*>(g_h2);
                const float x1v = __uint_as_float((uint32_t)__ldcg(x1p + (size_t)row * D_ + col) << 16);
                const float h2v = __uint_as_float((uint32_t)__ldcg(h2p + (size_t)row * D_ + col) << 16);
                const float gb = __ldcg(g_mod + 5 * D_ + col);
                P.out[(size_t)row * D_ + col] = __float2bfloat16_rn(x1v + bf16r(gb * bf16r(h2v + upd)));
            }
        }
    }
    if (ct == 0) TL_MAX(5);
    bar_sync(1, 256);
    if (ct == 0) {
        __threadfence();
        const uint32_t n = atomicAdd(&g_exitCount, 1);
        if (n + 1 == ep1 * (uint32_t)nG) { g_jobCounter[0] = 0; g_jobCounter[1] = 0; __threadfence(); atomicAdd(&g_epoch, 1); }
    }
}
typedef CUresult (*PFN_encodeTiled)(CUtensorMap*, CUtensorMapDataType, cuuint32_t, void*, const cuuint64_t*, const cuuint64_t*,
                                    const cuuint32_t*, const cuuint32_t*, CUtensorMapInterleave, CUtensorMapSwizzle,
                                    CUtensorMapL2promotion, CUtensorMapFloatOOBfill);
static PFN_encodeTiled get_encode() {
    static PFN_encodeTiled fn = nullptr;
    if (!fn) {
        void* p = nullptr;
        cudaDriverEntryPointQueryResult qr;
        cudaGetDriverEntryPoint("cuTensorMapEncodeTiled", &p, cudaEnableDefault, &qr);
        fn = (PFN_encodeTiled)p;
    }
    return fn;
}
static void make_map(CUtensorMap* m, const void* ptr, uint64_t rows, uint64_t cols, uint32_t brows, uint32_t bcols) {
    cuuint64_t dims[2] = {cols, rows};
    cuuint64_t strides[1] = {cols * 2};
    cuuint32_t box[2] = {bcols, brows};
    cuuint32_t es[2] = {1, 1};
    get_encode()(m, CU_TENSOR_MAP_DATA_TYPE_BFLOAT16, 2, const_cast<void*>(ptr), dims, strides, box, es,
                 CU_TENSOR_MAP_INTERLEAVE_NONE, CU_TENSOR_MAP_SWIZZLE_128B, CU_TENSOR_MAP_L2_PROMOTION_L2_128B,
                 CU_TENSOR_MAP_FLOAT_OOB_FILL_NONE);
}
template <class T> static void* sym_addr(T& sym) { void* p = nullptr; cudaGetSymbolAddress(&p, sym); return p; }
struct HostState {
    bool init = false;
    const void* key[14];
    void* out = nullptr;
    RParams rp;
    GParams gp;
    int nG = 0;
};

extern "C" void kernel_launch(void* const* d_in, const int* in_sizes, int n_in, void* d_out, int out_size) {
    (void)in_sizes; (void)n_in; (void)out_size;
    static HostState hs;
    bool same = hs.init && hs.out == d_out;
    for (int i = 0; i < 14 && same; i++) same = (hs.key[i] == d_in[i]);
    if (!same) {
        for (int i = 0; i < 14; i++) hs.key[i] = d_in[i];
        hs.out = d_out;
        const void *Wq = d_in[2], *Wk = d_in[3], *Wv = d_in[4], *Wo = d_in[5];
        make_map(&hs.rp.tmWq, Wq, 512, 4096, 256, 64);
        make_map(&hs.rp.tmWk, Wk, 512, 4096, 256, 64);
        make_map(&hs.rp.tmWv, Wv, 512, 4096, 256, 64);
        make_map(&hs.rp.tmWo, Wo, 4096, 512, 128, 64);
        hs.rp.mem0 = (const bf16*)d_in[1];
        hs.rp.c = (const bf16*)d_in[12];
        hs.rp.w_mod = (const bf16*)d_in[13];
        hs.rp.x = (const bf16*)d_in[0];
        hs.rp.wo = (const bf16*)Wo;
        make_map(&hs.gp.tmWq, Wq, 512, 4096, 64, 64);
        make_map(&hs.gp.tmWk, Wk, 512, 4096, 64, 64);
        make_map(&hs.gp.tmWv, Wv, 512, 4096, 64, 64);
        make_map(&hs.gp.tmWo, Wo, 4096, 512, 64, 64);
        hs.gp.x = (const bf16*)d_in[0];
        hs.gp.w_r = (const bf16*)d_in[8];
        hs.gp.w_gate = (const bf16*)d_in[9];
        hs.gp.w_up = (const bf16*)d_in[10];
        hs.gp.w_down = (const bf16*)d_in[11];
        hs.gp.c = (const bf16*)d_in[12];
        hs.gp.w_mod = (const bf16*)d_in[13];
        hs.gp.out = (bf16*)d_out;
        int dev = 0, sms = 0;
        cudaGetDevice(&dev);
        cudaDeviceGetAttribute(&sms, cudaDevAttrMultiProcessorCount, dev);
        hs.nG = sms - 64;
        cudaFuncSetAttribute(r_kernel, cudaFuncAttributeNonPortableClusterSizeAllowed, 1);
        cudaFuncSetAttribute(r_kernel, cudaFuncAttributeMaxDynamicSharedMemorySize, R_SMEM);
        cudaFuncSetAttribute(g_kernel, cudaFuncAttributeMaxDynamicSharedMemorySize, G_SMEM);
        hs.init = true;
    }
    cudaStream_t st = cudaStreamPerThread;
    {
        cudaLaunchConfig_t cfg = {};
        cfg.gridDim = dim3(64); cfg.blockDim = dim3(R_THREADS); cfg.dynamicSmemBytes = R_SMEM; cfg.stream = st;
        cudaLaunchAttribute at[1];
        at[0].id = cudaLaunchAttributeClusterDimension;
        at[0].val.clusterDim.x = 16; at[0].val.clusterDim.y = 1; at[0].val.clusterDim.z = 1;
        cfg.attrs = at; cfg.numAttrs = 1;
        cudaLaunchKernelEx(&cfg, r_kernel, hs.rp);
    }
    {
        cudaLaunchConfig_t cfg = {};
        cfg.gridDim = dim3(hs.nG); cfg.blockDim = dim3(G_THREADS); cfg.dynamicSmemBytes = G_SMEM; cfg.stream = st;
        cudaLaunchAttribute at[1];
        at[0].id = cudaLaunchAttributeProgrammaticStreamSerialization;
        at[0].val.programmaticStreamSerializationAllowed = 1;
        cfg.attrs = at; cfg.numAttrs = 1;
        cudaLaunchKernelEx(&cfg, g_kernel, hs.gp);
    }
}
```
